```python
import torch

def _softmax(x, axis=-1):
    return torch.softmax(x, dim=axis)
def _gelu(x):
    return torch.nn.functional.gelu(x, approximate="tanh")
def _silu(x):
    return torch.nn.functional.silu(x)
def _sigmoid(x):
    return torch.sigmoid(x)
def _layernorm(x, axis=-1, eps=1e-5):
    m = x.mean(dim=axis, keepdim=True)
    v = x.var(dim=axis, keepdim=True, unbiased=False)
    return (x - m) / torch.sqrt(v + eps)
def _scatter_add(tgt, idx, src, axis=0):
    return tgt.clone().index_add_(axis, idx, src)
def _segment_sum(src, seg, n):
    out = torch.zeros((n,) + src.shape[1:], dtype=src.dtype)
    return out.index_add_(0, seg, src)
def _pad(x, pw):
    flat = tuple(v for pair in reversed(pw) for v in pair)
    return torch.nn.functional.pad(x, flat)

kernel_name = 'standalone__deep_cross_fibinet__recsys'

def setup_inputs():

    _w = (lambda a: (lambda t: t.to(torch.bfloat16) if t.is_floating_point() else t)(torch.as_tensor(a)))
    B, F, D = 4096, 26, 64
    V = min(100000, 100000)
    Fr = max(F // 2, 1)
    H = min(F * D, 256)
    return {
        "idx": _w((lambda lo, hi, *s: torch.randint(lo, hi, s))(0, V, B, F).to(torch.int64)),
        "table": _w((lambda *s: torch.randn(*s, dtype=torch.bfloat16) * 1.6)(V, D)),
        "se_w1": _w((lambda *s: torch.randn(*s, dtype=torch.bfloat16) * 1.6)(F, Fr)),
        "se_w2": _w((lambda *s: torch.randn(*s, dtype=torch.bfloat16) * 1.6)(Fr, F)),
        "w_bi": _w((lambda *s: torch.randn(*s, dtype=torch.bfloat16) * 0.05)(D, D) * (D ** -0.5)),
        "w_cross": _w((lambda *s: torch.randn(*s, dtype=torch.bfloat16) * 0.05)(2 * F * F * D) * 0.01),
        "w_deep1": _w((lambda *s: torch.randn(*s, dtype=torch.bfloat16) * 0.8)(F * D, H) * ((F * D) ** -0.5)),
        "w_deep2": _w((lambda *s: torch.randn(*s, dtype=torch.bfloat16) * 0.05)(H) * 0.01),
    }

def reference(idx, table, se_w1, se_w2, w_bi, w_cross, w_deep1, w_deep2):
    emb = table[idx]
    B = emb.shape[0]
    z = emb.mean(axis=-1)
    a = _sigmoid(_gelu(z @ se_w1) @ se_w2)
    v = a[:, :, None] * emb
    eW = torch.einsum('bfd,de->bfe', emb, w_bi)
    vW = torch.einsum('bfd,de->bfe', v, w_bi)
    p = torch.einsum('bie,bje->bije', eW, emb).reshape(B, -1)
    q = torch.einsum('bie,bje->bije', vW, v).reshape(B, -1)
    cross_feat = torch.concatenate([p, q], axis=-1)
    logit_cross = cross_feat @ w_cross
    h = _gelu(emb.reshape(B, -1) @ w_deep1)
    logit_deep = h @ w_deep2
    return logit_cross + logit_deep
```

```cpp
#include <cuda_runtime.h>
#include <cuda_bf16.h>
#include <cuda.h>
#include <stdint.h>
#include <type_traits>
#include <utility>

#define R_DEEP 200
#define R_CR1 144
#define R_CR2 216
#define R_DEEP2 56
#define R_PROD 24

namespace {

constexpr int NF = 26, ND = 64, NH = 256, NFR = 13;

#define TS(slot)
#define TSL(slot)

__device__ __forceinline__ uint32_t smem_u32(const void* p) { return (uint32_t)__cvta_generic_to_shared(p); }
__device__ __forceinline__ void mbar_init(uint32_t bar, uint32_t cnt) {
    asm volatile("mbarrier.init.shared::cta.b64 [%0], %1;" ::"r"(bar), "r"(cnt));
}
__device__ __forceinline__ void mbar_expect_tx(uint32_t bar, uint32_t bytes) {
    asm volatile("mbarrier.arrive.expect_tx.shared::cta.b64 _, [%0], %1;" ::"r"(bar), "r"(bytes) : "memory");
}
__device__ __forceinline__ void mbar_arrive(uint32_t bar) {
    asm volatile("mbarrier.arrive.shared::cta.b64 _, [%0];" ::"r"(bar) : "memory");
}
__device__ __forceinline__ void mbar_wait(uint32_t bar, uint32_t parity) {
    asm volatile(
        "{\n"
        ".reg .pred p;\n"
        "WAIT_%=:\n"
        "mbarrier.try_wait.parity.shared::cta.b64 p, [%0], %1;\n"
        "@p bra.uni DONE_%=;\nbra.uni WAIT_%=;\nDONE_%=:\n"
        "}\n" ::"r"(bar),
        "r"(parity)
        : "memory");
}
__device__ __forceinline__ bool mbar_test(uint32_t bar, uint32_t parity) {
    uint32_t r;
    asm volatile("{\n.reg .pred p;\nmbarrier.test_wait.parity.shared::cta.b64 p, [%1], %2;\nselp.u32 %0, 1, 0, p;\n}\n" : "=r"(r) : "r"(bar), "r"(parity) : "memory");
    return r;
}
__device__ __forceinline__ uint32_t opq(uint32_t x) { return __shfl_xor_sync(0xffffffffu, x, 0); }
__device__ __forceinline__ uint64_t uni64(uint64_t x) {
    uint32_t lo = (uint32_t)x, hi = (uint32_t)(x >> 32);
    asm volatile("shfl.sync.idx.b32 %0, %0, 0, 31, -1;\nshfl.sync.idx.b32 %1, %1, 0, 31, -1;" : "+r"(lo), "+r"(hi));
    return ((uint64_t)hi << 32) | lo;
}
__device__ __forceinline__ bool elect_one() {
    uint32_t r;
    asm volatile("{\n.reg .pred p;\nelect.sync _|p, 0xffffffff;\nselp.u32 %0, 1, 0, p;\n}\n" : "=r"(r));
    return r;
}
__device__ __forceinline__ const void* row_ptr(const void* base, uint32_t i) {
    const void* r;
    asm("mad.wide.u32 %0, %1, 128, %2;" : "=l"(r) : "r"(i), "l"(base));
    return r;
}
__device__ __forceinline__ void mbar_wait_bounded(uint32_t bar, uint32_t parity) {
    asm volatile(
        "{\n"
        ".reg .pred p;\n"
        ".reg .u32 c;\n"
        "mov.u32 c, 0;\n"
        "WAIT_%=:\n"
        "mbarrier.try_wait.parity.shared::cta.b64 p, [%0], %1;\n"
        "@p bra.uni DONE_%=;\n"
        "add.u32 c, c, 1;\n"
        "setp.lt.u32 p, c, 0x400000;\n"
        "@p bra.uni WAIT_%=;\n"
        "trap;\n"
        "DONE_%=:\n"
        "}\n" ::"r"(bar),
        "r"(parity)
        : "memory");
}
__device__ __forceinline__ void cp_async16(uint32_t dst, const void* src) {
    asm volatile("cp.async.cg.shared.global [%0], [%1], 16;" ::"r"(dst), "l"(src) : "memory");
}
__device__ __forceinline__ void cp_async_commit() { asm volatile("cp.async.commit_group;" ::: "memory"); }
template <int N> __device__ __forceinline__ void cp_async_wait() { asm volatile("cp.async.wait_group %0;" ::"n"(N) : "memory"); }
__device__ __forceinline__ void cp_async_mbar_arrive_noinc(uint32_t bar) {
    asm volatile("cp.async.mbarrier.arrive.noinc.shared::cta.b64 [%0];" ::"r"(bar) : "memory");
}
__device__ __forceinline__ void tma_load_3d(uint32_t dst, const void* tmap, int c0, int c1, int c2, uint32_t bar) {
    asm volatile(
        "cp.async.bulk.tensor.3d.shared::cluster.global.mbarrier::complete_tx::bytes [%0], [%1, {%3, %4, %5}], [%2];" ::"r"(dst),
        "l"(tmap), "r"(bar), "r"(c0), "r"(c1), "r"(c2)
        : "memory");
}
__device__ __forceinline__ void bulk_load(uint32_t dst, const void* src, uint32_t bytes, uint32_t bar) {
    asm volatile("cp.async.bulk.shared::cluster.global.mbarrier::complete_tx::bytes [%0], [%1], %2, [%3];" ::"r"(dst), "l"(src), "r"(bytes),
                 "r"(bar)
                 : "memory");
}
__device__ __forceinline__ void fence_proxy_async() { asm volatile("fence.proxy.async.shared::cta;" ::: "memory"); }
__device__ __forceinline__ void wgmma_fence() { asm volatile("wgmma.fence.sync.aligned;" ::: "memory"); }
__device__ __forceinline__ void wgmma_commit() { asm volatile("wgmma.commit_group.sync.aligned;" ::: "memory"); }
template <int N> __device__ __forceinline__ void wgmma_wait() { asm volatile("wgmma.wait_group.sync.aligned %0;" ::"n"(N) : "memory"); }

__device__ __forceinline__ void ldsm_x4(uint32_t addr, uint32_t& r0, uint32_t& r1, uint32_t& r2, uint32_t& r3) {
    asm volatile("ldmatrix.sync.aligned.m8n8.x4.shared.b16 {%0,%1,%2,%3}, [%4];" : "=r"(r0), "=r"(r1), "=r"(r2), "=r"(r3) : "r"(addr));
}
__device__ __forceinline__ void ldsm_x4_t(uint32_t addr, uint32_t& r0, uint32_t& r1, uint32_t& r2, uint32_t& r3) {
    asm volatile("ldmatrix.sync.aligned.m8n8.x4.trans.shared.b16 {%0,%1,%2,%3}, [%4];" : "=r"(r0), "=r"(r1), "=r"(r2), "=r"(r3) : "r"(addr));
}
__device__ __forceinline__ void stsm_x4_t(uint32_t addr, uint32_t r0, uint32_t r1, uint32_t r2, uint32_t r3) {
    asm volatile("stmatrix.sync.aligned.m8n8.x4.trans.shared.b16 [%0], {%1,%2,%3,%4};" ::"r"(addr), "r"(r0), "r"(r1), "r"(r2), "r"(r3) : "memory");
}
__device__ __forceinline__ uint4 lds128(uint32_t addr) {
    uint4 v;
    asm volatile("ld.shared.v4.u32 {%0,%1,%2,%3}, [%4];" : "=r"(v.x), "=r"(v.y), "=r"(v.z), "=r"(v.w) : "r"(addr));
    return v;
}
__device__ __forceinline__ uint32_t lds32(uint32_t addr) {
    uint32_t v;
    asm volatile("ld.shared.u32 %0, [%1];" : "=r"(v) : "r"(addr));
    return v;
}
__device__ __forceinline__ void sts128(uint32_t addr, uint32_t a, uint32_t b, uint32_t c, uint32_t d) {
    asm volatile("st.shared.v4.u32 [%0], {%1,%2,%3,%4};" ::"r"(addr), "r"(a), "r"(b), "r"(c), "r"(d) : "memory");
}
__device__ __forceinline__ void mma16816(float (&c)[4], uint32_t a0, uint32_t a1, uint32_t a2, uint32_t a3, uint32_t b0, uint32_t b1) {
    asm("mma.sync.aligned.m16n8k16.row.col.f32.bf16.bf16.f32 {%0,%1,%2,%3}, {%4,%5,%6,%7}, {%8,%9}, {%0,%1,%2,%3};"
        : "+f"(c[0]), "+f"(c[1]), "+f"(c[2]), "+f"(c[3])
        : "r"(a0), "r"(a1), "r"(a2), "r"(a3), "r"(b0), "r"(b1));
}
__device__ __forceinline__ uint32_t pack_bf16(float lo, float hi) {
    uint32_t r;
    asm("cvt.rn.bf16x2.f32 %0, %1, %2;" : "=r"(r) : "f"(hi), "f"(lo));
    return r;
}
__device__ __forceinline__ float bf_lo(uint32_t x) { return __uint_as_float(x << 16); }
__device__ __forceinline__ float bf_hi(uint32_t x) { return __uint_as_float(x & 0xffff0000u); }
__device__ __forceinline__ uint32_t hmul2_bf16(uint32_t a, uint32_t b) {
    uint32_t r;
    asm("mul.rn.bf16x2 %0, %1, %2;" : "=r"(r) : "r"(a), "r"(b));
    return r;
}
__device__ __forceinline__ float tanh_fast(float x) {
    float r;
    asm("tanh.approx.f32 %0, %1;" : "=f"(r) : "f"(x));
    return r;
}
__device__ __forceinline__ float gelu_tanh(float x) {
    const float k0 = 0.7978845608028654f, k01 = 0.7978845608028654f * 0.044715f;
    const float u = x * fmaf(x * x, k01, k0);
    const float hx = 0.5f * x;
    return fmaf(hx, tanh_fast(u), hx);
}

__device__ __forceinline__ uint32_t gelu2x2(uint32_t w) {
    const float k0 = 0.7978845608028654f, k01 = 0.7978845608028654f * 0.044715f;
    const float x = bf_lo(w), y = bf_hi(w);
    return pack_bf16(fmaf(x, tanh_fast(x * fmaf(x * x, k01, k0)), x), fmaf(y, tanh_fast(y * fmaf(y * y, k01, k0)), y));
}
__device__ __forceinline__ float sigmoid_f(float x) { return fmaf(tanh_fast(0.5f * x), 0.5f, 0.5f); }

#define WG_ACC8(c, b) c(acc[b]), c(acc[b + 1]), c(acc[b + 2]), c(acc[b + 3]), c(acc[b + 4]), c(acc[b + 5]), c(acc[b + 6]), c(acc[b + 7])
#define WG_N128(c, sc)                                                                                                              \
    asm volatile(                                                                                                                   \
        "{\n"                                                                                                                       \
        ".reg .pred p;\n"                                                              \
        "setp.ne.b32 p, " sc ", 0;\n"                                                                                               \
        "wgmma.mma_async.sync.aligned.m64n128k16.f32.bf16.bf16 "                                                                    \
        "{%0,%1,%2,%3,%4,%5,%6,%7,%8,%9,%10,%11,%12,%13,%14,%15,"                                                                   \
        "%16,%17,%18,%19,%20,%21,%22,%23,%24,%25,%26,%27,%28,%29,%30,%31,"                                                          \
        "%32,%33,%34,%35,%36,%37,%38,%39,%40,%41,%42,%43,%44,%45,%46,%47,"                                                          \
        "%48,%49,%50,%51,%52,%53,%54,%55,%56,%57,%58,%59,%60,%61,%62,%63},"                                                         \
        " {%64,%65,%66,%67}, %68, p, 1, 1, 1;\n"                                                                                    \
        "}\n"                                                                                                                       \
        : WG_ACC8(c, 0), WG_ACC8(c, 8), WG_ACC8(c, 16), WG_ACC8(c, 24), WG_ACC8(c, 32), WG_ACC8(c, 40), WG_ACC8(c, 48), WG_ACC8(c, 56) \
        : "r"(a[0]), "r"(a[1]), "r"(a[2]), "r"(a[3]), "l"(db), "r"(scv))
__device__ __forceinline__ void wgmma_m64n128k16_rs_tb(float (&acc)[64], const uint32_t (&a)[4], uint64_t db, int scv) {
    WG_N128("+f", "%69");
}
#define WG_N40(c, sc)                                                                         \
    asm volatile(                                                                             \
        "{\n"                                                                                 \
        ".reg .pred p;\n"                        \
        "setp.ne.b32 p, " sc ", 0;\n"                                                         \
        "wgmma.mma_async.sync.aligned.m64n40k16.f32.bf16.bf16 "                               \
        "{%0,%1,%2,%3,%4,%5,%6,%7,%8,%9,%10,%11,%12,%13,%14,%15,%16,%17,%18,%19},"            \
        " {%20,%21,%22,%23}, %24, p, 1, 1, 1;\n"                                              \
        "}\n"                                                                                 \
        : WG_ACC8(c, 0), WG_ACC8(c, 8), c(acc[16]), c(acc[17]), c(acc[18]), c(acc[19])        \
        : "r"(a[0]), "r"(a[1]), "r"(a[2]), "r"(a[3]), "l"(db))
template <int SC>
__device__ __forceinline__ void wgmma_m64n40k16_rs_tb(float (&acc)[20], const uint32_t (&a)[4], uint64_t db) {
    if constexpr (SC == 1) WG_N40("+f", "1");
    else if constexpr (SC == 2) WG_N40("+f", "0");
    else WG_N40("=f", "0");
}
#define WG_N32(c, sc)                                                   \
    asm volatile(                                                       \
        "{\n"                                                           \
        ".reg .pred p;\n"           \
        "setp.ne.b32 p, " sc ", 0;\n"                                   \
        "wgmma.mma_async.sync.aligned.m64n32k16.f32.bf16.bf16 "         \
        "{%0,%1,%2,%3,%4,%5,%6,%7,%8,%9,%10,%11,%12,%13,%14,%15},"      \
        " {%16,%17,%18,%19}, %20, p, 1, 1, 0;\n"                        \
        "}\n"                                                           \
        : WG_ACC8(c, 0), WG_ACC8(c, 8)                                  \
        : "r"(a0), "r"(a1), "r"(a2), "r"(a3), "l"(db))
template <int SC>
__device__ __forceinline__ void wgmma_m64n32k16_rs(float (&acc)[16], uint32_t a0, uint32_t a1, uint32_t a2, uint32_t a3, uint64_t db) {
    if constexpr (SC == 1) WG_N32("+f", "1");
    else if constexpr (SC == 2) WG_N32("+f", "0");
    else WG_N32("=f", "0");
}

__host__ __device__ constexpr uint64_t make_desc(uint32_t addr, uint32_t lbo_bytes, uint32_t sbo_bytes, uint32_t swz) {
    uint64_t d = 0;
    d |= (uint64_t)((addr & 0x3FFFF) >> 4);
    d |= (uint64_t)((lbo_bytes >> 4) & 0x3FFF) << 16;
    d |= (uint64_t)((sbo_bytes >> 4) & 0x3FFF) << 32;
    d |= (uint64_t)swz << 62;
    return d;
}
__device__ __forceinline__ uint32_t ldg_u16(const __nv_bfloat16* p) { return (uint32_t)__ldg(reinterpret_cast<const unsigned short*>(p)); }
__device__ __forceinline__ uint32_t ldg_bf16_pair(const __nv_bfloat16* p0, bool v0, const __nv_bfloat16* p1, bool v1) {
    const uint32_t lo = v0 ? ldg_u16(p0) : 0u;
    const uint32_t hi = v1 ? ldg_u16(p1) : 0u;
    return lo | (hi << 16);
}
template <int N, class F, int... I>
__device__ __forceinline__ void static_for_impl(F&& f, std::integer_sequence<int, I...>) {
    (f(std::integral_constant<int, N + I>{}), ...);
}
template <int B, int E, class F>
__device__ __forceinline__ void static_for(F&& f) {
    static_for_impl<B>(f, std::make_integer_sequence<int, E - B>{});
}

__device__ __forceinline__ uint32_t hfma2_bf16(uint32_t a, uint32_t b, uint32_t c) {
    uint32_t r;
    asm("fma.rn.bf16x2 %0, %1, %2, %3;" : "=r"(r) : "r"(a), "r"(b), "r"(c));
    return r;
}
__device__ __forceinline__ float gelu2(float x) {
    const float k0 = 0.7978845608028654f, k01 = 0.7978845608028654f * 0.044715f;
    return fmaf(x, tanh_fast(x * fmaf(x * x, k01, k0)), x);
}
__device__ __forceinline__ uint32_t gelu2p(uint32_t x) {
    uint32_t t;
    const uint32_t u = hmul2_bf16(x, hfma2_bf16(hmul2_bf16(x, x), 0x3D123D12u, 0x3F4C3F4Cu));
    asm("tanh.approx.bf16x2 %0, %1;" : "=r"(t) : "r"(u));
    return hfma2_bf16(x, t, x);
}
__device__ __forceinline__ void wgmma_m64n8k16_rs(float (&acc)[4], const uint32_t* a, uint64_t db, int sc) {
    asm volatile("{\n.reg .pred p;\nsetp.ne.b32 p, %9, 0;\nwgmma.mma_async.sync.aligned.m64n8k16.f32.bf16.bf16 {%0,%1,%2,%3}, {%4,%5,%6,%7}, %8, p, 1, 1, 0;\n}\n"
                 : "+f"(acc[0]), "+f"(acc[1]), "+f"(acc[2]), "+f"(acc[3])
                 : "r"(a[0]), "r"(a[1]), "r"(a[2]), "r"(a[3]), "l"(db), "r"(sc));
}

template <int SC>
__device__ __forceinline__ void wgmma_m64n16k16_rs(float (&acc)[8], const uint32_t* a, uint64_t db) {
    asm volatile("{\n.reg .pred p;\nsetp.ne.b32 p, %13, 0;\nwgmma.mma_async.sync.aligned.m64n16k16.f32.bf16.bf16 {%0,%1,%2,%3,%4,%5,%6,%7}, {%8,%9,%10,%11}, %12, p, 1, 1, 0;\n}\n"
                 : WG_ACC8("+f", 0)
                 : "r"(a[0]), "r"(a[1]), "r"(a[2]), "r"(a[3]), "l"(db), "n"(SC));
}

constexpr int SB0 = 1024;
constexpr int SLOT = 4096;
constexpr int EWP = SLOT + 16;
constexpr int OFF_EW = 608;
constexpr int OFF_RT = 1024;
constexpr int RT = 8192;
constexpr int OFF_TW = OFF_RT + 13 * RT;
constexpr int HS_BYTES = 16384;
constexpr int OFF_RING = OFF_RT + 17 * RT;
constexpr int OFF_WBI = OFF_RING + 4 * HS_BYTES;
constexpr int OFF_IDX = OFF_WBI + 8192;
constexpr int OFF_SEF = OFF_IDX + 8192;
constexpr int ZP = 144;
constexpr int OFF_Z = OFF_SEF + 2048 + 128;
constexpr int OFF_W2 = 0;
constexpr int OFF_DP = OFF_Z + 32 * ZP;
constexpr int OFF_ID = OFF_DP + 6 * 32 * 4;
constexpr int OFF_BAR = OFF_ID + 256;
constexpr int TILE = 2048;
constexpr int CHUNK = 4 * TILE;
constexpr int NCHUNK = 16;
constexpr int CPOS = 0x15403261;
static_assert(OFF_TW + 14 * CHUNK == OFF_SEF && OFF_EW + 25 * EWP + SLOT <= OFF_TW, "layout");
static_assert(OFF_RING % 1024 == 0 && OFF_WBI % 1024 == 0 && OFF_ID % 128 == 0, "align");
constexpr int B_CFULL = 0,
              B_W = 16,
              B_EMPTY = 48, B_ZRDY = B_EMPTY + NF, B_CDONE = B_ZRDY + 1,
              B_EWRDY = B_CDONE + 2, B_PAIR = 80,
              B_IDX = B_PAIR + 13, B_FIN = B_PAIR + 14;
constexpr int OFF_TS = OFF_BAR + 768;
constexpr int SMEM = OFF_TS + 512;
static_assert(SMEM <= 232448, "smem");
constexpr int NFIRST = 4;
#define UNR 4
#define PF0 11
#define WI 0
#define PFD 4
#define NEARLY 1
constexpr int NUNIT = 128;

__device__ __align__(1024) uint8_t g_wt[2 * NCHUNK * CHUNK];
__device__ unsigned int g_cnt;

__device__ __forceinline__ void pick(uint32_t (&M)[8][12], int h, uint32_t a0, uint32_t a1, uint32_t act) {
    asm volatile(
        "{\n.reg .pred p;\nsetp.ne.u32 p, %99, 0;\n"
        "TS_%=: .branchtargets L0_%=, L1_%=, L2_%=, L3_%=, L4_%=, L5_%=;\n"
        "brx.idx.uni %96, TS_%=;\n"
        "L0_%=: @p ld.shared.v4.u32 {%0,%12,%24,%36}, [%97+0]; @p ld.shared.v4.u32 {%2,%14,%26,%38}, [%97+1024]; @p ld.shared.v4.u32 {%48,%60,%72,%84}, [%98+0]; @p ld.shared.v4.u32 {%50,%62,%74,%86}, [%98+1024]; bra.uni END_%=;\n"
        "L1_%=: @p ld.shared.v4.u32 {%1,%13,%25,%37}, [%97+0]; @p ld.shared.v4.u32 {%3,%15,%27,%39}, [%97+1024]; @p ld.shared.v4.u32 {%49,%61,%73,%85}, [%98+0]; @p ld.shared.v4.u32 {%51,%63,%75,%87}, [%98+1024]; bra.uni END_%=;\n"
        "L2_%=: @p ld.shared.v4.u32 {%4,%16,%28,%40}, [%97+0]; @p ld.shared.v4.u32 {%6,%18,%30,%42}, [%97+1024]; @p ld.shared.v4.u32 {%52,%64,%76,%88}, [%98+0]; @p ld.shared.v4.u32 {%54,%66,%78,%90}, [%98+1024]; bra.uni END_%=;\n"
        "L3_%=: @p ld.shared.v4.u32 {%5,%17,%29,%41}, [%97+0]; @p ld.shared.v4.u32 {%7,%19,%31,%43}, [%97+1024]; @p ld.shared.v4.u32 {%53,%65,%77,%89}, [%98+0]; @p ld.shared.v4.u32 {%55,%67,%79,%91}, [%98+1024]; bra.uni END_%=;\n"
        "L4_%=: @p ld.shared.v4.u32 {%8,%20,%32,%44}, [%97+0]; @p ld.shared.v4.u32 {%10,%22,%34,%46}, [%97+1024]; @p ld.shared.v4.u32 {%56,%68,%80,%92}, [%98+0]; @p ld.shared.v4.u32 {%58,%70,%82,%94}, [%98+1024]; bra.uni END_%=;\n"
        "L5_%=: @p ld.shared.v4.u32 {%9,%21,%33,%45}, [%97+0]; @p ld.shared.v4.u32 {%11,%23,%35,%47}, [%97+1024]; @p ld.shared.v4.u32 {%57,%69,%81,%93}, [%98+0]; @p ld.shared.v4.u32 {%59,%71,%83,%95}, [%98+1024]; \n"
        "END_%=:\n"
        "}\n"
        : "+r"(M[0][0]), "+r"(M[0][1]), "+r"(M[0][2]), "+r"(M[0][3]), "+r"(M[0][4]), "+r"(M[0][5]), "+r"(M[0][6]), "+r"(M[0][7]), "+r"(M[0][8]), "+r"(M[0][9]), "+r"(M[0][10]), "+r"(M[0][11]), "+r"(M[1][0]), "+r"(M[1][1]), "+r"(M[1][2]), "+r"(M[1][3]), "+r"(M[1][4]), "+r"(M[1][5]), "+r"(M[1][6]), "+r"(M[1][7]), "+r"(M[1][8]), "+r"(M[1][9]), "+r"(M[1][10]), "+r"(M[1][11]), "+r"(M[2][0]), "+r"(M[2][1]), "+r"(M[2][2]), "+r"(M[2][3]), "+r"(M[2][4]), "+r"(M[2][5]), "+r"(M[2][6]), "+r"(M[2][7]), "+r"(M[2][8]), "+r"(M[2][9]), "+r"(M[2][10]), "+r"(M[2][11]), "+r"(M[3][0]), "+r"(M[3][1]), "+r"(M[3][2]), "+r"(M[3][3]), "+r"(M[3][4]), "+r"(M[3][5]), "+r"(M[3][6]), "+r"(M[3][7]), "+r"(M[3][8]), "+r"(M[3][9]), "+r"(M[3][10]), "+r"(M[3][11]), "+r"(M[4][0]), "+r"(M[4][1]), "+r"(M[4][2]), "+r"(M[4][3]), "+r"(M[4][4]), "+r"(M[4][5]), "+r"(M[4][6]), "+r"(M[4][7]), "+r"(M[4][8]), "+r"(M[4][9]), "+r"(M[4][10]), "+r"(M[4][11]), "+r"(M[5][0]), "+r"(M[5][1]), "+r"(M[5][2]), "+r"(M[5][3]), "+r"(M[5][4]), "+r"(M[5][5]), "+r"(M[5][6]), "+r"(M[5][7]), "+r"(M[5][8]), "+r"(M[5][9]), "+r"(M[5][10]), "+r"(M[5][11]), "+r"(M[6][0]), "+r"(M[6][1]), "+r"(M[6][2]), "+r"(M[6][3]), "+r"(M[6][4]), "+r"(M[6][5]), "+r"(M[6][6]), "+r"(M[6][7]), "+r"(M[6][8]), "+r"(M[6][9]), "+r"(M[6][10]), "+r"(M[6][11]), "+r"(M[7][0]), "+r"(M[7][1]), "+r"(M[7][2]), "+r"(M[7][3]), "+r"(M[7][4]), "+r"(M[7][5]), "+r"(M[7][6]), "+r"(M[7][7]), "+r"(M[7][8]), "+r"(M[7][9]), "+r"(M[7][10]), "+r"(M[7][11])
        : "r"(h), "r"(a0), "r"(a1), "r"(act));
}

__device__ __forceinline__ void u_lda(uint32_t (&A)[8], uint32_t a0, uint32_t a1) {
    ldsm_x4_t(a0, A[0], A[1], A[2], A[3]);
    ldsm_x4_t(a1, A[4], A[5], A[6], A[7]);
}
__device__ __forceinline__ void u_mma(float (&acc)[16], const uint32_t (&A)[8], uint64_t desc) {
    wgmma_m64n32k16_rs<2>(acc, A[0], A[1], A[2], A[3], desc);
    wgmma_m64n32k16_rs<1>(acc, A[4], A[5], A[6], A[7], desc + 64);
}
__device__ __forceinline__ void send_partial(uint32_t sb, int src, int w4, int g, int t, float v0, float v1) {
    asm volatile("barrier.cluster.wait.acquire.aligned;" ::: "memory");
    if (t < 2) {
        uint32_t rb;
        asm volatile("mapa.shared::cluster.u32 %0, %1, %2;" : "=r"(rb) : "r"(sb), "r"(w4 >> 1));
        asm volatile("st.async.weak.shared::cluster.mbarrier::complete_tx::bytes.f32 [%0], %1, [%2];" ::"r"(rb + OFF_DP + (src * 32 + (w4 & 1) * 16 + 8 * t + g) * 4),
                     "f"(t ? v1 : v0), "r"(rb + OFF_BAR + B_FIN * 8)
                     : "memory");
    }
}

__global__ void __cluster_dims__(2, 1, 1) __launch_bounds__(512, 1)
fused_kernel(const __grid_constant__ CUtensorMap tmW1, const int* __restrict__ idx, const __nv_bfloat16* __restrict__ table,
             const __nv_bfloat16* __restrict__ se_w1, const __nv_bfloat16* __restrict__ se_w2, const __nv_bfloat16* __restrict__ w_bi,
             const __nv_bfloat16* __restrict__ w_cross, const __nv_bfloat16* __restrict__ w1, const __nv_bfloat16* __restrict__ w2,
             __nv_bfloat16* __restrict__ out) {
    extern __shared__ __align__(1024) uint8_t smem_raw[];
    const uint32_t sb = __shfl_sync(0xffffffffu, smem_u32(smem_raw), 0);
    if ((sb & 0xFFFFFFu) != SB0) __trap();
    const uint32_t bars = sb + OFF_BAR;
#define BAR(i) (bars + (i) * 8)
    const int tid = threadIdx.x, warp = __shfl_sync(0xffffffffu, tid >> 5, 0), lane = tid & 31, g = lane >> 2, t = lane & 3;
    const int rank = blockIdx.x & 1;
    const int pb0 = (blockIdx.x >> 1) * 64;
    if (tid == 0) TS(0);
    const int b = (tid >> 3) & 31;
    const int2* ipg = reinterpret_cast<const int2*>(idx + (pb0 + b) * NF);
    const int2 i0a = __ldg(ipg), i0b = __ldg(ipg + 16 * NF), i1a = __ldg(ipg + 1), i1b = __ldg(ipg + 16 * NF + 1);
    if (elect_one()) {
        mbar_init(BAR(B_PAIR + warp), warp < 13 ? 256 + (warp == 6) : 1);
        mbar_init(BAR(16 + warp), (warp & 1) ? 9 : 1);
        if (warp >= 13 || warp < NEARLY) {
            asm volatile("fence.mbarrier_init.release.cluster;" ::: "memory");
            mbar_expect_tx(BAR(warp < NEARLY ? B_W + warp : B_PAIR + warp), warp < NEARLY ? HS_BYTES : warp == 13 ? 64 * NF * 4 : 6 * 32 * 4);
            if (warp == 13) bulk_load(sb + OFF_IDX, idx + pb0 * NF, 64 * NF * 4, BAR(B_IDX));
            if (warp < NEARLY) tma_load_3d(sb + OFF_RING + (warp + 2) * HS_BYTES, &tmW1, 0, warp * 64, rank * 2, BAR(B_W + warp));
        }
        if (warp == 6) asm volatile("cp.async.bulk.prefetch.L2.global [%0], %1;" ::"l"((const char*)w1 + 4 * 32768 + blockIdx.x * 5632), "n"(5632) : "memory");
        mbar_init(BAR(32 + warp), (warp & 1) ? 9 : 1);
        mbar_init(BAR(48 + warp), 4);
        mbar_init(BAR(64 + warp), warp == B_CDONE - 64 ? 8 : 4);
        mbar_init(BAR(warp), (0x2321 >> (4 * warp)) & 3 | (warp > 3));
        asm volatile("fence.mbarrier_init.release.cluster;" ::: "memory");
    }
    __syncthreads();
    asm volatile("barrier.cluster.arrive.relaxed.aligned;" ::: "memory");
    if (tid == 0) TS(1);

    if (warp >= 12) {
        asm volatile("setmaxnreg.dec.sync.aligned.u32 %0;" ::"n"(R_PROD));
        if (warp == 12) {
#pragma unroll 1
            for (int f = NEARLY; f < NF; f++) {
                if (f >= 4) mbar_wait_bounded(BAR(B_EMPTY + f - 4), 0);
                TSL(80 + f);
                if (elect_one()) {
                    mbar_expect_tx(BAR(B_W + f), HS_BYTES);
                    tma_load_3d(sb + OFF_RING + ((f + 2) & 3) * HS_BYTES, &tmW1, 0, f * 64, rank * 2, BAR(B_W + f));

                }
            }
            asm volatile("barrier.cluster.wait.acquire.aligned;" ::: "memory");
            mbar_wait_bounded(BAR(B_FIN), 0);
            float v = 0.f;
#pragma unroll
            for (int i = 0; i < 6; i++) v += __uint_as_float(lds32(sb + OFF_DP + (i * 32 + lane) * 4));
            out[pb0 + 32 * rank + lane] = __float2bfloat16_rn(v);
            TSL(15);
        } else {
            if (warp == 14) {
#pragma unroll 1
                for (int k = 2; k < NF; k++) {
                    mbar_wait(BAR(B_PAIR + min((k + 3) >> 1, 12)), 0);
                    mbar_wait(BAR(B_W + k), 0);
                    asm volatile("bar.arrive %0, 160;" ::"r"(4 + (k & 3)) : "memory");
                }
            } else if (warp == 13) {
                const uint32_t sr = sb + OFF_RT + 16 * RT;
                {
                    uint32_t v[12];
#pragma unroll
                    for (int i = 0; i < 12; i++) v[i] = lane + 32 * (i >> 1) < NF * NFR / 2 ? __ldg(reinterpret_cast<const uint32_t*>((i & 1) ? se_w2 : se_w1) + lane + 32 * (i >> 1)) : 0u;
#pragma unroll
                    for (int i = 0; i < 12; i++) asm volatile("st.shared.u32 [%0], %1;" ::"r"(sr + lane * 4 + (i >> 1) * 128 + (i & 1) * 1024), "r"(v[i]) : "memory");
                    __syncwarp();
                }
#pragma unroll 1
                for (int q = 0; q < 8; q++) {
                    const int c1 = 8 * (q & 1) + g, o1 = c1 < NFR ? min((8 * (q >> 1) + 2 * t) * NFR + c1, NF * NFR) : NF * NFR;
                    const int c2 = 8 * (q & 3) + ((q & 3) < 3 ? 4 * (g & 1) + (g >> 1) : (g & 1)), o2 = min((8 * (q >> 2) + 2 * t) * NF + c2, NF * NFR);
                    uint32_t y1, y2;
                    asm volatile("{\n.reg .b16 a, b, c, d;\nld.shared.b16 a, [%2];\nld.shared.b16 b, [%2 + 26];\nld.shared.b16 c, [%3 + 1024];\nld.shared.b16 d, [%3 + 1076];\n"
                                 "mov.b32 %0, {a, b};\nmov.b32 %1, {c, d};\n}\n" : "=r"(y1), "=r"(y2) : "r"(sr + 2 * o1), "r"(sr + 2 * o2));
                    asm volatile("st.shared.u32 [%0], %1;\nst.shared.u32 [%0 + 1024], %2;" ::"r"(sb + OFF_SEF + q * 128 + lane * 4), "r"(y1),
                                 "r"(hmul2_bf16(y2, 0x3E803E80u))
                                 : "memory");
                }
                fence_proxy_async();
                __syncwarp();
                TSL(12);
                if (elect_one()) mbar_arrive(BAR(B_PAIR + 6));
                const uint32_t ia = sb + OFF_IDX + (32 * rank + lane) * NF * 4;
                mbar_wait(BAR(B_IDX), 0);
                uint32_t x[4];
                asm volatile("ld.shared.v2.u32 {%0,%1}, [%4];\nld.shared.v2.u32 {%2,%3}, [%4 + 8];" : "=r"(x[0]), "=r"(x[1]), "=r"(x[2]), "=r"(x[3]) : "r"(ia + 88));
                mbar_wait(BAR(B_EMPTY + 8), 0);
#pragma unroll
                for (int i = 0; i < 4; i++) asm volatile("prefetch.global.L2 [%0];" ::"l"(row_ptr(table, x[i])));
            } else {
                {
                    const int pq = blockIdx.x >> 6, js = (blockIdx.x >> 1) & 31;
                    const int j = js < 24 ? (js & 24) + 4 * (js & 1) + ((js >> 1) & 3) : 24 + (js & 1);
                    const bool on = js < 24 || ((js >> 1) & 3) == ((lane >> 2) & 3);
                    const __nv_bfloat16* s = w_cross + ((size_t)(pq * NF) * NF + j) * ND + 32 * rank + lane;
                    uint8_t* d = g_wt + (size_t)rank * NCHUNK * CHUNK + (((lane & 15) >> 1) * 2 + (lane >> 4)) * CHUNK + ((lane & 1) * 2 + pq) * TILE + js * 16;
#pragma unroll 1
                    for (int kh = 0; kh < 2; kh++) {
                        uint32_t x[8];
#pragma unroll
                        for (int k = 0; k < 8; k++)
                            x[k] = (on && (kh == 0 || k < 5)) ? ldg_u16(s + (k + (k & 4)) * NF * ND) | (ldg_u16(s + (k == 4 && kh ? 9 : k + (k & 4) + 4) * NF * ND) << 16) : 0u;
                        *reinterpret_cast<uint4*>(d) = make_uint4(x[0], x[1], x[2], x[3]);
                        *reinterpret_cast<uint4*>(d + 512) = make_uint4(x[4], x[5], x[6], x[7]);
                        s += 16 * NF * ND;
                        d += 1024;
                    }
                    __syncwarp();
                }
                TSL(8);
                if (elect_one()) asm volatile("red.release.gpu.global.inc.u32 [%0], %1;" ::"l"(&g_cnt), "n"(NUNIT + 127) : "memory");
                TSL(9);
                mbar_wait(BAR(B_EMPTY + 6), 0);
                TSL(10);
                unsigned int v;
                do {
                    asm volatile("ld.acquire.gpu.global.u32 %0, [%1];" : "=r"(v) : "l"(&g_cnt) : "memory");
                } while (v < NUNIT);
                asm volatile("fence.proxy.async.global;" ::: "memory");
                __syncwarp();
                if (elect_one()) asm volatile("red.relaxed.gpu.global.inc.u32 [%0], %1;" ::"l"(&g_cnt), "n"(NUNIT + 127) : "memory");
                TSL(11);
                const uint8_t* wsrc = g_wt + (size_t)rank * NCHUNK * CHUNK;
#pragma unroll 1
                for (int k = 0; k < 8; k++) {
                    mbar_wait(BAR(B_EMPTY + 20 + ((0x75493260 >> (4 * k)) & 15)), 0);
                    TSL(30 + k);
                    if (elect_one()) {
                        const uint32_t cf = BAR(B_CFULL + ((0x33222110 >> (4 * k)) & 3));
                        mbar_expect_tx(cf, 2 * CHUNK);
                        bulk_load(sb + OFF_TW + ((CPOS >> (4 * k)) & 7) * 2 * CHUNK, wsrc + k * 2 * CHUNK, 2 * CHUNK, cf);
                    }
                }
            }
            __syncwarp();
            asm volatile("barrier.cluster.wait.acquire.aligned;" ::: "memory");
        }
    } else if (warp < 4) {
        {
            const uint4* wb = reinterpret_cast<const uint4*>(w_bi + (tid >> 2) * 64 + 32 * rank + 8 * t);
            const uint4 wb0 = __ldg(wb), wb1 = __ldg(wb + 256);
            const uint32_t w2v = __ldg(reinterpret_cast<const uint32_t*>(w2) + rank * 64 + (tid & 63));
            if (tid < 64) sts128(sb + OFF_WBI + tid * 128 + ((4 ^ (tid & 7)) << 4), 0x3C80u, 0u, 0u, 0u);
            else sts128(sb + OFF_Z + ((tid - 64) >> 1) * ZP + 96 + (tid & 1) * 16, 0u, 0u, 0u, 0u);
            asm volatile("st.shared.u32 [%0], %1;" ::"r"(sb + OFF_ID + (tid & 63) * 4), "r"(0x3F803F80u) : "memory");
            asm volatile("st.shared.u32 [%0], %1;" ::"r"(sb + OFF_W2 + (tid & 56) * 4 + (tid & 3) * 8 + (tid & 4)), "r"(w2v) : "memory");
            const uint32_t wd = sb + OFF_WBI + (tid >> 2) * 128 + ((t ^ (g & 7)) << 4);
            sts128(wd, wb0.x, wb0.y, wb0.z, wb0.w);
            sts128(wd + 4096, wb1.x, wb1.y, wb1.z, wb1.w);
            fence_proxy_async();
        }
        asm volatile("setmaxnreg.inc.sync.aligned.u32 %0;" ::"n"(R_DEEP));
        asm volatile("bar.sync 1, 128;" ::: "memory");
        TS(7);
        float acc[64];
        float e2[2][20];
#pragma unroll
        for (int i = 0; i < 64; i++) asm volatile("" : "=f"(acc[i]));
#pragma unroll
        for (int i = 0; i < 20; i++) asm volatile("" : "=f"(e2[0][i]), "=f"(e2[1][i]));
        uint32_t A[4][4][4];
        constexpr uint64_t dr = make_desc(SB0 + OFF_RING, 8192, 1024, 1), dwc = make_desc(SB0 + OFF_WBI, 4096, 1024, 1);
        const uint64_t dw = uni64(dwc + (sb >> 28));
        const uint32_t sa = opq((lane >> 4) * 128 + (2 * warp + ((lane >> 3) & 1)) * 512 + (lane & 7) * 16);
        const uint32_t za = opq((8 * warp + g) * ZP);
        const uint32_t ln = opq(lane);
        const bool l0 = ln == 0, t0 = (ln & 3) == 0;
        uint32_t la[4];
#pragma unroll
        for (int i = 0; i < 4; i++) la[i] = opq((sb + OFF_RT + (16 * warp + (lane & 15)) * 128 + (((lane >> 4) ^ (lane & 7)) << 4)) ^ (i << 5));
        auto cvt = [&](uint32_t (&pk)[9], const float (&e)[20]) {
#pragma unroll
            for (int i = 0; i < 9; i++) asm volatile("cvt.rn.bf16x2.f32 %0, %1, %2;" : "=r"(pk[i]) : "f"(e[i < 8 ? 2 * i + 1 : 18]), "f"(e[2 * i]));
        };
        auto store = [&](const uint32_t (&pk)[9], uint32_t so, uint32_t zo) {
            stsm_x4_t(sa + so, pk[0], pk[1], pk[2], pk[3]);
            stsm_x4_t(sa + so + 256, pk[4], pk[5], pk[6], pk[7]);
            if (t0) asm volatile("st.shared.b32 [%0], %1;" ::"r"(za + zo), "r"(pk[8]) : "memory");
        };
        auto load1 = [&](auto VC, int i, uint32_t o) {
            constexpr int v = decltype(VC)::value;
            ldsm_x4(la[i ^ (2 * (v & 1))] + o, A[v][i][0], A[v][i][1], A[v][i][2], A[v][i][3]);
        };
        auto mma_e = [&](auto VC) {
            constexpr int v = decltype(VC)::value;
            uint32_t(&ai)[4][4] = A[v];
            wgmma_m64n40k16_rs_tb<2>(e2[v & 1], ai[0], dw);
            wgmma_m64n40k16_rs_tb<1>(e2[v & 1], ai[1], dw + 128);
            wgmma_m64n40k16_rs_tb<1>(e2[v & 1], ai[2], dw + 256);
            wgmma_m64n40k16_rs_tb<1>(e2[v & 1], ai[3], dw + 384);
        };
        auto mma_d1 = [&](auto VC, int i, int sc) {
            constexpr int v = decltype(VC)::value, st = (v + 2) & 3;
            wgmma_m64n128k16_rs_tb(acc, A[v][i], dr + st * (HS_BYTES >> 4) + 128 * i, sc);
        };
        auto mma_d = [&](auto VC, int sc) {
            wgmma_fence();
#pragma unroll
            for (int i = 0; i < 4; i++) mma_d1(VC, i, i ? 1 : sc);
            wgmma_commit();
        };
        auto mma_e1 = [&](auto VC) {
            wgmma_fence();
            mma_e(VC);
            wgmma_commit();
        };
        auto load = [&](auto VC, uint32_t o) {
#pragma unroll
            for (int i = 0; i < 4; i++) load1(VC, i, o);
        };
#define READY(k) asm volatile("bar.sync %0, 160;" ::"n"(4 + ((k) & 3)) : "memory")
        using I0 = std::integral_constant<int, 0>;
        using I1 = std::integral_constant<int, 1>;
        using I2 = std::integral_constant<int, 2>;
        using I3 = std::integral_constant<int, 3>;
        uint32_t pk[9];
        mbar_wait(BAR(B_PAIR), 0);
        TS(19);
        load(I0{}, 0);
        load(I1{}, 6 * RT);
        mma_e1(I0{});
        mbar_wait(BAR(B_W), 0);
        mma_d(I0{}, 0);
        mma_e1(I1{});
        mbar_wait(BAR(B_W + 1), 0);
        mma_d(I1{}, 1);
        mbar_wait(BAR(B_PAIR + 1), 0);
        TS(20);
        load(I2{}, RT);
        load(I3{}, 7 * RT);
        wgmma_wait<2>();
        if (l0) mbar_arrive(BAR(B_EMPTY));
        cvt(pk, e2[0]);
        mbar_wait(BAR(B_PAIR + 2), 0);
        wgmma_wait<0>();
#pragma unroll 1
        for (int j = 0; j < 20; j += 4) {
            const uint32_t zu = sb + OFF_Z + j * 4, su = sb + OFF_EW + j * EWP;
            static_for<0, 4>([&](auto UU) {
                constexpr int u = decltype(UU)::value;
                std::integral_constant<int, (u + 2) & 3> UC;
                store(pk, su + u * EWP, zu + u * 4);
                load(UU, (u == 3 && j == 16 ? j - 8 : j) * (RT / 2) + ((u + 4 + 11 * (u & 1)) / 2) * RT);
                mma_e1(UC);
                READY(u + 2);
                mma_d(UC, 1);
                wgmma_wait<2>();
                if (l0) mbar_arrive(BAR(B_EMPTY + 1 + u) + j * 8);
                cvt(pk, e2[(u + 1) & 1]);
            });
            mbar_wait_bounded(BAR(B_IDX), 0);
        }
        {
            uint32_t p2[9];
            store(pk, sb + OFF_EW + 20 * EWP, sb + OFF_Z + 80);
            load(I0{}, 12 * RT);
            mma_e1(I2{});
            wgmma_wait<2>();
            cvt(pk, e2[1]);
            mma_e1(I3{});
            store(pk, sb + OFF_EW + 21 * EWP, sb + OFF_Z + 84);
            READY(22);
            READY(23);
            wgmma_wait<2>();
            if (l0) mbar_arrive(BAR(B_EMPTY + 21));
            load(I1{}, 14 * RT);
            wgmma_wait<1>();
            cvt(pk, e2[0]);
            mma_e1(I0{});
            store(pk, sb + OFF_EW + 22 * EWP, sb + OFF_Z + 88);
            wgmma_wait<1>();
            cvt(pk, e2[1]);
            mma_e1(I1{});
            mma_d(I2{}, 1);
            store(pk, sb + OFF_EW + 23 * EWP, sb + OFF_Z + 92);
            wgmma_wait<1>();
            if (t0) asm volatile("st.shared.v2.b32 [%0], {%1,%2};" ::"r"(za + sb + OFF_Z + 96), "r"(pack_bf16(e2[0][16], e2[0][18])), "r"(pack_bf16(e2[1][16], e2[1][18])) : "memory");
            __syncwarp();
            if (l0) mbar_arrive(BAR(B_ZRDY));
            TS(2);
            mma_d(I3{}, 1);
            wgmma_wait<1>();
            if (l0) mbar_arrive(BAR(B_EMPTY + 22));
            READY(24);
            mma_d(I0{}, 1);
            cvt(pk, e2[0]);
            cvt(p2, e2[1]);
            READY(25);
            stsm_x4_t(sa + sb + OFF_EW + 24 * EWP, pk[0], pk[1], pk[2], pk[3]);
            stsm_x4_t(sa + sb + OFF_EW + 24 * EWP + 256, pk[4], pk[5], pk[6], pk[7]);
            stsm_x4_t(sa + sb + OFF_EW + 25 * EWP, p2[0], p2[1], p2[2], p2[3]);
            stsm_x4_t(sa + sb + OFF_EW + 25 * EWP + 256, p2[4], p2[5], p2[6], p2[7]);
            wgmma_wait<1>();
            __syncwarp();
            if (ln < 2) mbar_arrive(ln ? BAR(B_EWRDY) : BAR(B_EMPTY + 23));
            mma_d(I1{}, 1);
            wgmma_wait<1>();
            if (l0) mbar_arrive(BAR(B_EMPTY + 24));
            TS(3);
        }
        {
            wgmma_wait<0>();
            if (l0) mbar_arrive(BAR(B_EMPTY + 25));
            uint32_t hw[32];
#pragma unroll
            for (int i = 0; i < 32; i++) asm volatile("cvt.rn.bf16x2.f32 %0, %1, %2;" : "=r"(hw[i]) : "f"(acc[2 * i + 1]), "f"(acc[2 * i]));
            asm volatile("setmaxnreg.dec.sync.aligned.u32 %0;" ::"n"(R_DEEP2));
            TS(4);
            float o[4] = {0.f, 0.f, 0.f, 0.f};
            int l2;
            asm volatile("mov.u32 %0, %%laneid;" : "=r"(l2));
#pragma unroll
            for (int it = 0; it < 8; it++) {
                uint32_t b0, b1;
                asm volatile("ld.shared.v2.u32 {%0,%1}, [%2];" : "=r"(b0), "=r"(b1) : "r"(sb + OFF_W2 + 8 * (l2 & 3) + it * 32));
                mma16816(o, gelu2p(hw[4 * it]), gelu2p(hw[4 * it + 1]), gelu2p(hw[4 * it + 2]), gelu2p(hw[4 * it + 3]), b0, b1);
            }
            send_partial(sb, rank * 3, warp, l2 >> 2, l2 & 3, 0.5f * o[0], 0.5f * o[2]);
        }
        TS(5);
    } else {
        const int wgc = (warp >> 2) - 1, w4 = warp & 3;
        const char* so = (const char*)table + 16 * (lane & 7);
        auto rp = [&](uint32_t i) { return row_ptr(so, i); };
        const uint32_t d0 = opq(sb + OFF_RT + b * 128 + (((lane ^ b) & 7) << 4)), d1 = opq((d0 ^ 64) + 6 * RT);
        {
            const int ia[4] = {i0a.x, i0a.y, i1a.x, i1a.y}, ib[4] = {i0b.x, i0b.y, i1b.x, i1b.y};
            static_for<0, NFIRST>([&](auto FC) {
                constexpr int f = decltype(FC)::value, o = (f >> 1) * RT;
                cp_async16(((f & 1) ? d1 : d0) + o, rp(ia[f]));
                cp_async16(((f & 1) ? d1 : d0) + o + 4096, rp(ib[f]));
                if (f & 1) cp_async_mbar_arrive_noinc(BAR(B_PAIR + (f >> 1)));
            });
            if (wgc == 0) TS(6);
        }
        asm volatile("setmaxnreg.inc.sync.aligned.u32 %0;" ::"n"(R_CR1));
        uint32_t M[8][12], y[4][2];
        {
            const uint32_t pa = opq(sb + OFF_RT + (t & 1) * 6 * RT + (16 * w4 + g) * 128 + (((4 * rank + 2 * wgc) ^ g ^ (4 * (t & 1))) << 4)), t1 = opq(t);
            const uint32_t ia = opq(sb + OFF_IDX + b * NF * 4);
#pragma unroll
            for (int i = 0; i < 96; i++) asm volatile("" : "=r"(M[i / 12][i % 12]));
            mbar_wait(BAR(B_IDX), 0);
            uint32_t x[2][2];
            auto load_idx = [&](int p) {
                asm volatile("ld.shared.v2.u32 {%0,%1}, [%2];" : "=r"(x[0][0]), "=r"(x[1][0]) : "r"(ia + p * 8));
                asm volatile("ld.shared.v2.u32 {%0,%1}, [%2];" : "=r"(x[0][1]), "=r"(x[1][1]) : "r"(ia + p * 8 + 32 * NF * 4));
            };
            load_idx(2);
#pragma unroll 1
            for (int q = -3; q < 12; q++) {
                const int p = (int)(0xCB00A9876005432ull >> (4 * q + 12)) & 15;
                if (q > 2) mbar_wait(BAR(B_EMPTY + 2 * q - 6), 0);
                if (p) {
                    const uint32_t o1 = (p > 10 ? p - 4 : p) * RT;
                    cp_async16(d0 + p * RT, rp(x[0][0]));
                    cp_async16(d0 + p * RT + 4096, rp(x[0][1]));
                    cp_async16(d1 + o1, rp(x[1][0]));
                    cp_async16(d1 + o1 + 4096, rp(x[1][1]));
                    cp_async_mbar_arrive_noinc(BAR(B_PAIR + p));
                    load_idx(p + 1);
                }
                if (q >= 0) {
                    mbar_wait(BAR(B_PAIR + q), 0);
                    const uint32_t ad = pa + q * RT - (q == 11 ? (t1 & 1) * 4 * RT : 0);
                    pick(M, q >> 1, ad, ad ^ 16, (t1 >> 1) == (q & 1));
                    __syncwarp();
                    if (elect_one()) mbar_arrive(BAR(B_W + 2 * q + 1));
                }
            }
            const uint32_t ta = sb + OFF_RT + 12 * RT + (16 * w4 + g) * 128 + (((4 * rank + 2 * wgc + (t >> 1)) ^ g) << 4) + 8 * (t & 1);
            mbar_wait(BAR(B_PAIR + 12), 0);
#pragma unroll
            for (int k = 0; k < 4; k++) asm volatile("ld.shared.v2.u32 {%0,%1}, [%2];" : "=r"(y[k][0]), "=r"(y[k][1]) : "r"(((k & 1) ? (ta ^ 64) + 2 * RT : ta) + (k >> 1) * 1024));
            __syncwarp();
            if (elect_one()) mbar_arrive(BAR(B_W + 25));
        }
        uint32_t TL[4][2];
        uint32_t ap[8], a0, a1;
        float o[16];
        {
            const uint32_t zb = sb + OFF_Z + (8 * w4 + g) * ZP + t * 8;
            mbar_wait(BAR(B_ZRDY), 0);
            uint32_t za[8];
#pragma unroll
            for (int i = 0; i < 4; i++) {
                uint32_t w0, w1;
                asm volatile("ld.shared.v2.u32 {%0,%1}, [%2];" : "=r"(w0), "=r"(w1) : "r"(zb + i * 32));
                za[2 * i] = __byte_perm(w0, w1, 0x5410);
                za[2 * i + 1] = __byte_perm(w0, w1, 0x7632);
            }
            constexpr uint64_t d1 = make_desc(SB0 + OFF_SEF, 256, 128, 0), d2 = make_desc(SB0 + OFF_SEF + 1024, 512, 128, 0);
            float h[8];
#pragma unroll
            for (int i = 0; i < 16; i++) asm volatile("" : "=f"(o[i]), "=f"(h[i & 7]));
            wgmma_fence();
            wgmma_m64n16k16_rs<0>(h, za, d1);
            wgmma_m64n16k16_rs<1>(h, za + 4, d1 + 32);
            wgmma_commit();
            wgmma_wait<0>();
            const uint32_t ha0 = pack_bf16(gelu2(h[0]), gelu2(h[1])), ha1 = pack_bf16(gelu2(h[2]), gelu2(h[3])), ha2 = pack_bf16(gelu2(h[4]), gelu2(h[5])),
                           ha3 = pack_bf16(gelu2(h[6]), gelu2(h[7]));
            wgmma_fence();
            wgmma_m64n32k16_rs<2>(o, ha0, ha1, ha2, ha3, d2);
            wgmma_commit();
            wgmma_wait<0>();
        }
        mbar_wait(BAR(B_CFULL), 0);
        mbar_wait(BAR(B_EWRDY), 0);
        if (wgc == 0) TS(60);
        asm volatile("setmaxnreg.inc.sync.aligned.u32 %0;" ::"n"(R_CR2));
        if (wgc == 0) TS(61);
        {
            int l2;
            asm volatile("mov.u32 %0, %%laneid;" : "=r"(l2));
            const int r = l2 & 7, bh = (l2 >> 3) & 1, ig = l2 >> 4;
            const uint32_t x = sb + OFF_EW + wgc * 256 + (2 * w4 + bh) * 512 + (8 * ig + 4 * (r & 1) + (r >> 1)) * EWP;
            a0 = opq(x);
            a1 = opq(x + (!ig || r == 0 ? 16 : r == 1 ? 13 : 8) * EWP);
        }
        constexpr uint64_t dt = make_desc(SB0 + OFF_TW, 512, 128, 0), dqc = make_desc(SB0 + OFF_ID, 128, 128, 0);
        const uint64_t dq = uni64(dqc + (sb >> 28));
        const uint64_t desc = dt + wgc * (CHUNK >> 4);
        auto dsc = [&](int e, int pq) { return desc + ((CPOS >> (4 * (e >> 1))) & 7) * (2 * CHUNK >> 4) + ((e & 1) * 2 + pq) * (TILE >> 4); };
        float S[4], accP[16], accQ[16];
#pragma unroll
        for (int i = 0; i < 16; i++) asm volatile("" : "=f"(accP[i]), "=f"(accQ[i]));
        uint32_t A0[8], A1[8], Aq[8], w[8];
        u_lda(A0, a0, a1);
        u_lda(A1, a0 + 16, a1 + 16);
#pragma unroll
        for (int k = 0; k < 8; k++) {
            float x, y;
            asm volatile("tanh.approx.f32 %0, %2;\ntanh.approx.f32 %1, %3;" : "=f"(x), "=f"(y) : "f"(o[2 * k]), "f"(o[2 * k + 1]));
            ap[k] = pack_bf16(fmaf(x, 0.5f, 0.5f), fmaf(y, 0.5f, 0.5f));
        }
#pragma unroll
        for (int k = 0; k < 8; k++) asm volatile("prmt.b32 %0, %1, %2, %3;" : "=r"(TL[k >> 1][k & 1]) : "r"(y[2 * (k & 1)][k >> 2]), "r"(y[2 * (k & 1) + 1][k >> 2]), "r"(0x5410 + 0x2222 * ((k >> 1) & 1)));
#pragma unroll
        for (int i = 0; i < 4; i++) asm volatile("" : "=f"(S[i]));
#pragma unroll
        for (int k = 0; k < 8; k++) Aq[k] = hmul2_bf16(A0[k], ap[k]);
        wgmma_fence();
        u_mma(accP, A0, dsc(0, 0));
        wgmma_commit();
        u_mma(accQ, Aq, dsc(0, 1));
        wgmma_commit();
        if (wgc == 0) TS(62);
        auto pack8 = [&](uint32_t (&d)[8], const float (&a)[16]) {
#pragma unroll
            for (int k = 0; k < 8; k++) asm volatile("cvt.rn.bf16x2.f32 %0, %1, %2;" : "=r"(d[k]) : "f"(a[2 * k + 1]), "f"(a[2 * k]));
        };
        static_for<0, 8>([&](auto PC) {
            constexpr int p = decltype(PC)::value, e = 2 * p;
            auto mw = [&](int s, int k) { return k < 6 ? __byte_perm(M[p][2 * k], M[p][2 * k + 1], s ? 0x7632 : 0x5410) : TL[(e + s) & 3][k - 6]; };
            uint32_t tp[8], tq[8];
            wgmma_wait<1>();
            pack8(tp, accP);
            wgmma_fence();
            u_mma(accP, A1, dsc(e + 1, 0));
            if (p) {
                wgmma_m64n8k16_rs(S, w, dq, p > 1);
                wgmma_m64n8k16_rs(S, w + 4, dq, 1);
            }
            wgmma_commit();
            if (p < 7) u_lda(A0, a0 + 16 * e + 32, a1 + 16 * e + 32);
            wgmma_wait<1>();
            pack8(tq, accQ);
#pragma unroll
            for (int k = 0; k < 8; k++) Aq[k] = hmul2_bf16(A1[k], ap[k]);
            wgmma_fence();
            u_mma(accQ, Aq, dsc(e + 1, 1));
            wgmma_commit();
#pragma unroll
            for (int k = 0; k < 8; k++) tq[k] = hfma2_bf16(tq[k], ap[k], tp[k]);
            if (p == 0 || p == 2 || p == 5) mbar_wait(BAR(B_CFULL + 1 + p / 2), 0);
            wgmma_wait<1>();
            pack8(tp, accP);
            if (p < 7) {
                wgmma_fence();
                u_mma(accP, A0, dsc(e + 2, 0));
                wgmma_commit();
                u_lda(A1, a0 + 16 * e + 48, a1 + 16 * e + 48);
            }
#pragma unroll
            for (int k = 0; k < 8; k++) w[k] = hmul2_bf16(tq[k], mw(0, k));
            wgmma_wait<(p < 7)>();
            if (p == 0 && elect_one()) mbar_arrive(BAR(B_CDONE));
            pack8(tq, accQ);
            if (p < 7) {
#pragma unroll
                for (int k = 0; k < 8; k++) Aq[k] = hmul2_bf16(A0[k], ap[k]);
                wgmma_fence();
                u_mma(accQ, Aq, dsc(e + 2, 1));
                wgmma_commit();
            }
#pragma unroll
            for (int k = 0; k < 8; k++) w[k] = hfma2_bf16(hfma2_bf16(tq[k], ap[k], tp[k]), mw(1, k), w[k]);
        });
        int tid2;
        asm volatile("mov.u32 %0, %%laneid;" : "=r"(tid2));
        wgmma_fence();
        wgmma_m64n8k16_rs(S, w, dq, 1);
        wgmma_m64n8k16_rs(S, w + 4, dq, 1);
        wgmma_commit();
        wgmma_wait<0>();
        send_partial(sb, rank * 3 + 1 + wgc, w4, tid2 >> 2, tid2 & 3, S[0], S[2]);
        if (wgc == 0) TS(14);
    }
#undef BAR
}

typedef CUresult (*PFN_encodeTiled)(CUtensorMap*, CUtensorMapDataType, cuuint32_t, void*, const cuuint64_t*, const cuuint64_t*,
                                    const cuuint32_t*, const cuuint32_t*, CUtensorMapInterleave, CUtensorMapSwizzle,
                                    CUtensorMapL2promotion, CUtensorMapFloatOOBfill);

}

extern "C" void kernel_launch(void* const* d_in, const int* in_sizes, int n_in, void* d_out, int out_size) {
    const int* idx = (const int*)d_in[0];
    const __nv_bfloat16* table = (const __nv_bfloat16*)d_in[1];
    const __nv_bfloat16* se_w1 = (const __nv_bfloat16*)d_in[2];
    const __nv_bfloat16* se_w2 = (const __nv_bfloat16*)d_in[3];
    const __nv_bfloat16* w_bi = (const __nv_bfloat16*)d_in[4];
    const __nv_bfloat16* w_cross = (const __nv_bfloat16*)d_in[5];
    const __nv_bfloat16* w_deep1 = (const __nv_bfloat16*)d_in[6];
    const __nv_bfloat16* w_deep2 = (const __nv_bfloat16*)d_in[7];
    __nv_bfloat16* out = (__nv_bfloat16*)d_out;

    static PFN_encodeTiled enc = nullptr;
    if (!enc) {
        void* fn = nullptr;
        cudaDriverEntryPointQueryResult qres;
        cudaGetDriverEntryPoint("cuTensorMapEncodeTiled", &fn, cudaEnableDefault, &qres);
        enc = (PFN_encodeTiled)fn;
        cudaFuncSetAttribute(fused_kernel, cudaFuncAttributeMaxDynamicSharedMemorySize, SMEM);
    }
    CUtensorMap tm;
    {
        cuuint64_t gdim[3] = {64, (cuuint64_t)(NF * ND), 4};
        cuuint64_t gstr[2] = {(cuuint64_t)NH * 2, 128};
        cuuint32_t box[3] = {64, 64, 2};
        cuuint32_t estr[3] = {1, 1, 1};
        enc(&tm, CU_TENSOR_MAP_DATA_TYPE_BFLOAT16, 3, (void*)w_deep1, gdim, gstr, box, estr, CU_TENSOR_MAP_INTERLEAVE_NONE,
            CU_TENSOR_MAP_SWIZZLE_128B, CU_TENSOR_MAP_L2_PROMOTION_L2_256B, CU_TENSOR_MAP_FLOAT_OOB_FILL_NONE);
    }
    fused_kernel<<<128, 512, SMEM>>>(tm, idx, table, se_w1, se_w2, w_bi, w_cross, w_deep1, w_deep2, out);
}
```

```cpp
#include <cuda_runtime.h>
#include <cuda_bf16.h>
#include <cuda.h>
#include <stdint.h>
#include <type_traits>
#include <utility>

#define R_DEEP 216
#define R_CR1 136
#define R_CR2 216
#define R_DEEP2 56
#define R_PROD 24

namespace {

constexpr int NF = 26, ND = 64, NH = 256, NFR = 13;

#define TS(slot)
#define TSL(slot)

__device__ __forceinline__ uint32_t smem_u32(const void* p) { return (uint32_t)__cvta_generic_to_shared(p); }
__device__ __forceinline__ void mbar_init(uint32_t bar, uint32_t cnt) {
    asm volatile("mbarrier.init.shared::cta.b64 [%0], %1;" ::"r"(bar), "r"(cnt));
}
__device__ __forceinline__ void mbar_expect_tx(uint32_t bar, uint32_t bytes) {
    asm volatile("mbarrier.arrive.expect_tx.shared::cta.b64 _, [%0], %1;" ::"r"(bar), "r"(bytes) : "memory");
}
__device__ __forceinline__ void mbar_arrive(uint32_t bar) {
    asm volatile("mbarrier.arrive.shared::cta.b64 _, [%0];" ::"r"(bar) : "memory");
}
__device__ __forceinline__ void mbar_wait(uint32_t bar, uint32_t parity) {
    asm volatile(
        "{\n"
        ".reg .pred p;\n"
        "WAIT_%=:\n"
        "mbarrier.try_wait.parity.shared::cta.b64 p, [%0], %1;\n"
        "@p bra.uni DONE_%=;\nbra.uni WAIT_%=;\nDONE_%=:\n"
        "}\n" ::"r"(bar),
        "r"(parity)
        : "memory");
}
__device__ __forceinline__ bool mbar_test(uint32_t bar, uint32_t parity) {
    uint32_t r;
    asm volatile("{\n.reg .pred p;\nmbarrier.test_wait.parity.shared::cta.b64 p, [%1], %2;\nselp.u32 %0, 1, 0, p;\n}\n" : "=r"(r) : "r"(bar), "r"(parity) : "memory");
    return r;
}
__device__ __forceinline__ uint32_t opq(uint32_t x) { return __shfl_xor_sync(0xffffffffu, x, 0); }
__device__ __forceinline__ uint64_t uni64(uint64_t x) {
    uint32_t lo = (uint32_t)x, hi = (uint32_t)(x >> 32);
    asm volatile("shfl.sync.idx.b32 %0, %0, 0, 31, -1;\nshfl.sync.idx.b32 %1, %1, 0, 31, -1;" : "+r"(lo), "+r"(hi));
    return ((uint64_t)hi << 32) | lo;
}
__device__ __forceinline__ bool elect_one() {
    uint32_t r;
    asm volatile("{\n.reg .pred p;\nelect.sync _|p, 0xffffffff;\nselp.u32 %0, 1, 0, p;\n}\n" : "=r"(r));
    return r;
}
__device__ __forceinline__ const void* row_ptr(const void* base, uint32_t i) {
    const void* r;
    asm("mad.wide.u32 %0, %1, 128, %2;" : "=l"(r) : "r"(i), "l"(base));
    return r;
}
__device__ __forceinline__ void mbar_wait_bounded(uint32_t bar, uint32_t parity) {
    asm volatile(
        "{\n"
        ".reg .pred p;\n"
        ".reg .u32 c;\n"
        "mov.u32 c, 0;\n"
        "WAIT_%=:\n"
        "mbarrier.try_wait.parity.shared::cta.b64 p, [%0], %1;\n"
        "@p bra.uni DONE_%=;\n"
        "add.u32 c, c, 1;\n"
        "setp.lt.u32 p, c, 0x400000;\n"
        "@p bra.uni WAIT_%=;\n"
        "trap;\n"
        "DONE_%=:\n"
        "}\n" ::"r"(bar),
        "r"(parity)
        : "memory");
}
__device__ __forceinline__ void cp_async16(uint32_t dst, const void* src) {
    asm volatile("cp.async.cg.shared.global [%0], [%1], 16;" ::"r"(dst), "l"(src) : "memory");
}
__device__ __forceinline__ void cp_async_commit() { asm volatile("cp.async.commit_group;" ::: "memory"); }
template <int N> __device__ __forceinline__ void cp_async_wait() { asm volatile("cp.async.wait_group %0;" ::"n"(N) : "memory"); }
__device__ __forceinline__ void cp_async_mbar_arrive_noinc(uint32_t bar) {
    asm volatile("cp.async.mbarrier.arrive.noinc.shared::cta.b64 [%0];" ::"r"(bar) : "memory");
}
__device__ __forceinline__ void tma_load_3d(uint32_t dst, const void* tmap, int c0, int c1, int c2, uint32_t bar) {
    asm volatile(
        "cp.async.bulk.tensor.3d.shared::cluster.global.mbarrier::complete_tx::bytes [%0], [%1, {%3, %4, %5}], [%2];" ::"r"(dst),
        "l"(tmap), "r"(bar), "r"(c0), "r"(c1), "r"(c2)
        : "memory");
}
__device__ __forceinline__ void bulk_load(uint32_t dst, const void* src, uint32_t bytes, uint32_t bar) {
    asm volatile("cp.async.bulk.shared::cluster.global.mbarrier::complete_tx::bytes [%0], [%1], %2, [%3];" ::"r"(dst), "l"(src), "r"(bytes),
                 "r"(bar)
                 : "memory");
}
__device__ __forceinline__ void fence_proxy_async() { asm volatile("fence.proxy.async.shared::cta;" ::: "memory"); }
__device__ __forceinline__ void wgmma_fence() { asm volatile("wgmma.fence.sync.aligned;" ::: "memory"); }
__device__ __forceinline__ void wgmma_commit() { asm volatile("wgmma.commit_group.sync.aligned;" ::: "memory"); }
template <int N> __device__ __forceinline__ void wgmma_wait() { asm volatile("wgmma.wait_group.sync.aligned %0;" ::"n"(N) : "memory"); }

__device__ __forceinline__ void ldsm_x4(uint32_t addr, uint32_t& r0, uint32_t& r1, uint32_t& r2, uint32_t& r3) {
    asm volatile("ldmatrix.sync.aligned.m8n8.x4.shared.b16 {%0,%1,%2,%3}, [%4];" : "=r"(r0), "=r"(r1), "=r"(r2), "=r"(r3) : "r"(addr));
}
__device__ __forceinline__ void ldsm_x4_t(uint32_t addr, uint32_t& r0, uint32_t& r1, uint32_t& r2, uint32_t& r3) {
    asm volatile("ldmatrix.sync.aligned.m8n8.x4.trans.shared.b16 {%0,%1,%2,%3}, [%4];" : "=r"(r0), "=r"(r1), "=r"(r2), "=r"(r3) : "r"(addr));
}
__device__ __forceinline__ void stsm_x4_t(uint32_t addr, uint32_t r0, uint32_t r1, uint32_t r2, uint32_t r3) {
    asm volatile("stmatrix.sync.aligned.m8n8.x4.trans.shared.b16 [%0], {%1,%2,%3,%4};" ::"r"(addr), "r"(r0), "r"(r1), "r"(r2), "r"(r3) : "memory");
}
__device__ __forceinline__ uint4 lds128(uint32_t addr) {
    uint4 v;
    asm volatile("ld.shared.v4.u32 {%0,%1,%2,%3}, [%4];" : "=r"(v.x), "=r"(v.y), "=r"(v.z), "=r"(v.w) : "r"(addr));
    return v;
}
__device__ __forceinline__ uint32_t lds32(uint32_t addr) {
    uint32_t v;
    asm volatile("ld.shared.u32 %0, [%1];" : "=r"(v) : "r"(addr));
    return v;
}
__device__ __forceinline__ void sts128(uint32_t addr, uint32_t a, uint32_t b, uint32_t c, uint32_t d) {
    asm volatile("st.shared.v4.u32 [%0], {%1,%2,%3,%4};" ::"r"(addr), "r"(a), "r"(b), "r"(c), "r"(d) : "memory");
}
__device__ __forceinline__ void mma16816(float (&c)[4], uint32_t a0, uint32_t a1, uint32_t a2, uint32_t a3, uint32_t b0, uint32_t b1) {
    asm("mma.sync.aligned.m16n8k16.row.col.f32.bf16.bf16.f32 {%0,%1,%2,%3}, {%4,%5,%6,%7}, {%8,%9}, {%0,%1,%2,%3};"
        : "+f"(c[0]), "+f"(c[1]), "+f"(c[2]), "+f"(c[3])
        : "r"(a0), "r"(a1), "r"(a2), "r"(a3), "r"(b0), "r"(b1));
}
__device__ __forceinline__ uint32_t pack_bf16(float lo, float hi) {
    uint32_t r;
    asm("cvt.rn.bf16x2.f32 %0, %1, %2;" : "=r"(r) : "f"(hi), "f"(lo));
    return r;
}
__device__ __forceinline__ float bf_lo(uint32_t x) { return __uint_as_float(x << 16); }
__device__ __forceinline__ float bf_hi(uint32_t x) { return __uint_as_float(x & 0xffff0000u); }
__device__ __forceinline__ uint32_t hmul2_bf16(uint32_t a, uint32_t b) {
    uint32_t r;
    asm("mul.rn.bf16x2 %0, %1, %2;" : "=r"(r) : "r"(a), "r"(b));
    return r;
}
__device__ __forceinline__ float tanh_fast(float x) {
    float r;
    asm("tanh.approx.f32 %0, %1;" : "=f"(r) : "f"(x));
    return r;
}
__device__ __forceinline__ float gelu_tanh(float x) {
    const float k0 = 0.7978845608028654f, k01 = 0.7978845608028654f * 0.044715f;
    const float u = x * fmaf(x * x, k01, k0);
    const float hx = 0.5f * x;
    return fmaf(hx, tanh_fast(u), hx);
}

__device__ __forceinline__ uint32_t gelu2x2(uint32_t w) {
    const float k0 = 0.7978845608028654f, k01 = 0.7978845608028654f * 0.044715f;
    const float x = bf_lo(w), y = bf_hi(w);
    return pack_bf16(fmaf(x, tanh_fast(x * fmaf(x * x, k01, k0)), x), fmaf(y, tanh_fast(y * fmaf(y * y, k01, k0)), y));
}
__device__ __forceinline__ float sigmoid_f(float x) { return fmaf(tanh_fast(0.5f * x), 0.5f, 0.5f); }

#define WG_ACC8(c, b) c(acc[b]), c(acc[b + 1]), c(acc[b + 2]), c(acc[b + 3]), c(acc[b + 4]), c(acc[b + 5]), c(acc[b + 6]), c(acc[b + 7])
#define WG_N128(c, sc)                                                                                                              \
    asm volatile(                                                                                                                   \
        "{\n"                                                                                                                       \
        ".reg .pred p;\n"                                                              \
        "setp.ne.b32 p, " sc ", 0;\n"                                                                                               \
        "wgmma.mma_async.sync.aligned.m64n128k16.f32.bf16.bf16 "                                                                    \
        "{%0,%1,%2,%3,%4,%5,%6,%7,%8,%9,%10,%11,%12,%13,%14,%15,"                                                                   \
        "%16,%17,%18,%19,%20,%21,%22,%23,%24,%25,%26,%27,%28,%29,%30,%31,"                                                          \
        "%32,%33,%34,%35,%36,%37,%38,%39,%40,%41,%42,%43,%44,%45,%46,%47,"                                                          \
        "%48,%49,%50,%51,%52,%53,%54,%55,%56,%57,%58,%59,%60,%61,%62,%63},"                                                         \
        " {%64,%65,%66,%67}, %68, p, 1, 1, 1;\n"                                                                                    \
        "}\n"                                                                                                                       \
        : WG_ACC8(c, 0), WG_ACC8(c, 8), WG_ACC8(c, 16), WG_ACC8(c, 24), WG_ACC8(c, 32), WG_ACC8(c, 40), WG_ACC8(c, 48), WG_ACC8(c, 56) \
        : "r"(a[0]), "r"(a[1]), "r"(a[2]), "r"(a[3]), "l"(db), "r"(scv))
__device__ __forceinline__ void wgmma_m64n128k16_rs_tb(float (&acc)[64], const uint32_t (&a)[4], uint64_t db, int scv) {
    WG_N128("+f", "%69");
}
#define WG_N40(c, sc)                                                                         \
    asm volatile(                                                                             \
        "{\n"                                                                                 \
        ".reg .pred p;\n"                        \
        "setp.ne.b32 p, " sc ", 0;\n"                                                         \
        "wgmma.mma_async.sync.aligned.m64n40k16.f32.bf16.bf16 "                               \
        "{%0,%1,%2,%3,%4,%5,%6,%7,%8,%9,%10,%11,%12,%13,%14,%15,%16,%17,%18,%19},"            \
        " {%20,%21,%22,%23}, %24, p, 1, 1, 1;\n"                                              \
        "}\n"                                                                                 \
        : WG_ACC8(c, 0), WG_ACC8(c, 8), c(acc[16]), c(acc[17]), c(acc[18]), c(acc[19])        \
        : "r"(a[0]), "r"(a[1]), "r"(a[2]), "r"(a[3]), "l"(db))
template <int SC>
__device__ __forceinline__ void wgmma_m64n40k16_rs_tb(float (&acc)[20], const uint32_t (&a)[4], uint64_t db) {
    if constexpr (SC == 1) WG_N40("+f", "1");
    else if constexpr (SC == 2) WG_N40("+f", "0");
    else WG_N40("=f", "0");
}
#define WG_N32(c, sc)                                                   \
    asm volatile(                                                       \
        "{\n"                                                           \
        ".reg .pred p;\n"           \
        "setp.ne.b32 p, " sc ", 0;\n"                                   \
        "wgmma.mma_async.sync.aligned.m64n32k16.f32.bf16.bf16 "         \
        "{%0,%1,%2,%3,%4,%5,%6,%7,%8,%9,%10,%11,%12,%13,%14,%15},"      \
        " {%16,%17,%18,%19}, %20, p, 1, 1, 0;\n"                        \
        "}\n"                                                           \
        : WG_ACC8(c, 0), WG_ACC8(c, 8)                                  \
        : "r"(a0), "r"(a1), "r"(a2), "r"(a3), "l"(db))
template <int SC>
__device__ __forceinline__ void wgmma_m64n32k16_rs(float (&acc)[16], uint32_t a0, uint32_t a1, uint32_t a2, uint32_t a3, uint64_t db) {
    if constexpr (SC == 1) WG_N32("+f", "1");
    else if constexpr (SC == 2) WG_N32("+f", "0");
    else WG_N32("=f", "0");
}

__host__ __device__ constexpr uint64_t make_desc(uint32_t addr, uint32_t lbo_bytes, uint32_t sbo_bytes, uint32_t swz) {
    uint64_t d = 0;
    d |= (uint64_t)((addr & 0x3FFFF) >> 4);
    d |= (uint64_t)((lbo_bytes >> 4) & 0x3FFF) << 16;
    d |= (uint64_t)((sbo_bytes >> 4) & 0x3FFF) << 32;
    d |= (uint64_t)swz << 62;
    return d;
}
__device__ __forceinline__ uint32_t ldg_u16(const __nv_bfloat16* p) { return (uint32_t)__ldg(reinterpret_cast<const unsigned short*>(p)); }
__device__ __forceinline__ uint32_t ldg_bf16_pair(const __nv_bfloat16* p0, bool v0, const __nv_bfloat16* p1, bool v1) {
    const uint32_t lo = v0 ? ldg_u16(p0) : 0u;
    const uint32_t hi = v1 ? ldg_u16(p1) : 0u;
    return lo | (hi << 16);
}
template <int N, class F, int... I>
__device__ __forceinline__ void static_for_impl(F&& f, std::integer_sequence<int, I...>) {
    (f(std::integral_constant<int, N + I>{}), ...);
}
template <int B, int E, class F>
__device__ __forceinline__ void static_for(F&& f) {
    static_for_impl<B>(f, std::make_integer_sequence<int, E - B>{});
}

__device__ __forceinline__ uint32_t hfma2_bf16(uint32_t a, uint32_t b, uint32_t c) {
    uint32_t r;
    asm("fma.rn.bf16x2 %0, %1, %2, %3;" : "=r"(r) : "r"(a), "r"(b), "r"(c));
    return r;
}
__device__ __forceinline__ float gelu2(float x) {
    const float k0 = 0.7978845608028654f, k01 = 0.7978845608028654f * 0.044715f;
    return fmaf(x, tanh_fast(x * fmaf(x * x, k01, k0)), x);
}
__device__ __forceinline__ uint32_t gelu2p(uint32_t x) {
    uint32_t t;
    const uint32_t u = hmul2_bf16(x, hfma2_bf16(hmul2_bf16(x, x), 0x3D123D12u, 0x3F4C3F4Cu));
    asm("tanh.approx.bf16x2 %0, %1;" : "=r"(t) : "r"(u));
    return hfma2_bf16(x, t, x);
}
__device__ __forceinline__ void wgmma_m64n8k16_rs(float (&acc)[4], const uint32_t* a, uint64_t db, int sc) {
    asm volatile("{\n.reg .pred p;\nsetp.ne.b32 p, %9, 0;\nwgmma.mma_async.sync.aligned.m64n8k16.f32.bf16.bf16 {%0,%1,%2,%3}, {%4,%5,%6,%7}, %8, p, 1, 1, 0;\n}\n"
                 : "+f"(acc[0]), "+f"(acc[1]), "+f"(acc[2]), "+f"(acc[3])
                 : "r"(a[0]), "r"(a[1]), "r"(a[2]), "r"(a[3]), "l"(db), "r"(sc));
}

template <int SC>
__device__ __forceinline__ void wgmma_m64n16k16_rs(float (&acc)[8], const uint32_t* a, uint64_t db) {
    asm volatile("{\n.reg .pred p;\nsetp.ne.b32 p, %13, 0;\nwgmma.mma_async.sync.aligned.m64n16k16.f32.bf16.bf16 {%0,%1,%2,%3,%4,%5,%6,%7}, {%8,%9,%10,%11}, %12, p, 1, 1, 0;\n}\n"
                 : WG_ACC8("+f", 0)
                 : "r"(a[0]), "r"(a[1]), "r"(a[2]), "r"(a[3]), "l"(db), "n"(SC));
}

constexpr int SB0 = 1024;
constexpr int SLOT = 4096;
constexpr int EWP = SLOT + 16;
constexpr int OFF_EW = 608;
constexpr int OFF_RT = 1024;
constexpr int RT = 8192;
constexpr int OFF_TW = OFF_RT + 13 * RT;
constexpr int HS_BYTES = 16384;
constexpr int OFF_RING = OFF_RT + 19 * RT;
constexpr int OFF_WBI = OFF_RT + 18 * RT;
constexpr int OFF_IDX = OFF_RT + 17 * RT;
constexpr int OFF_SEF = OFF_RING + 4 * HS_BYTES;
constexpr int OFF_AP = OFF_SEF + 2048;
constexpr int OFF_W2 = 0;
constexpr int OFF_DP = OFF_AP + 4096;
constexpr int OFF_ID = OFF_DP + 6 * 32 * 4;
constexpr int OFF_BAR = OFF_ID + 256;
constexpr int TILE = 2048;
constexpr int CHUNK = 4 * TILE;
constexpr int NCHUNK = 16;
constexpr int CPOS = 0x16504321;
static_assert(OFF_TW + 14 * CHUNK == OFF_SEF && OFF_EW + 25 * EWP + SLOT <= OFF_TW, "layout");
static_assert(OFF_RING % 1024 == 0 && OFF_WBI % 1024 == 0 && OFF_ID % 128 == 0, "align");
constexpr int B_CFULL = 0,
              B_W = 16,
              B_EMPTY = 48, B_ZRDY = B_EMPTY + NF, B_CDONE = B_ZRDY + 1,
              B_EWRDY = B_CDONE + 2, B_PAIR = 80,
              B_IDX = B_PAIR + 13, B_FIN = B_PAIR + 14;
constexpr int OFF_TS = OFF_BAR + 768;
constexpr int SMEM = OFF_TS + 512;
static_assert(SMEM <= 232448, "smem");
constexpr int NFIRST = 4;
#define UNR 4
#define PF0 11
#define WI 0
#define PACE 3
#define WPF 1
#define GT 0x0C0BA9876054302ull
#define PFD 4
#define NEARLY 0
constexpr int NUNIT = 128;

__device__ __align__(1024) uint8_t g_wt[2 * NCHUNK * CHUNK];
__device__ unsigned int g_cnt;

__device__ __forceinline__ void u_lda(uint32_t (&A)[8], uint32_t a0, uint32_t a1) {
    ldsm_x4_t(a0, A[0], A[1], A[2], A[3]);
    ldsm_x4_t(a1, A[4], A[5], A[6], A[7]);
}
__device__ __forceinline__ void u_mma(float (&acc)[16], const uint32_t (&A)[8], uint64_t desc) {
    wgmma_m64n32k16_rs<2>(acc, A[0], A[1], A[2], A[3], desc);
    wgmma_m64n32k16_rs<1>(acc, A[4], A[5], A[6], A[7], desc + 64);
}
__device__ __forceinline__ void send_partial(uint32_t sb, int src, int w4, int g, int t, float v0, float v1) {
    asm volatile("barrier.cluster.wait.acquire.aligned;" ::: "memory");
    if (t < 2) {
        uint32_t rb;
        asm volatile("mapa.shared::cluster.u32 %0, %1, %2;" : "=r"(rb) : "r"(sb), "r"(w4 >> 1));
        asm volatile("st.async.weak.shared::cluster.mbarrier::complete_tx::bytes.f32 [%0], %1, [%2];" ::"r"(rb + OFF_DP + (src * 32 + (w4 & 1) * 16 + 8 * t + g) * 4),
                     "f"(t ? v1 : v0), "r"(rb + OFF_BAR + B_FIN * 8)
                     : "memory");
    }
}

__global__ void __cluster_dims__(2, 1, 1) __launch_bounds__(512, 1)
fused_kernel(const __grid_constant__ CUtensorMap tmW1, const int* __restrict__ idx, const __nv_bfloat16* __restrict__ table,
             const __nv_bfloat16* __restrict__ se_w1, const __nv_bfloat16* __restrict__ se_w2, const __nv_bfloat16* __restrict__ w_bi,
             const __nv_bfloat16* __restrict__ w_cross, const __nv_bfloat16* __restrict__ w1, const __nv_bfloat16* __restrict__ w2,
             __nv_bfloat16* __restrict__ out) {
    extern __shared__ __align__(1024) uint8_t smem_raw[];
    const uint32_t sb = __shfl_sync(0xffffffffu, smem_u32(smem_raw), 0);
    if ((sb & 0xFFFFFFu) != SB0) __trap();
    const uint32_t bars = sb + OFF_BAR;
#define BAR(i) (bars + (i) * 8)
    const int tid = threadIdx.x, warp = __shfl_sync(0xffffffffu, tid >> 5, 0), lane = tid & 31, g = lane >> 2, t = lane & 3;
    const int rank = blockIdx.x & 1;
    const int pb0 = (blockIdx.x >> 1) * 64;
    if (tid == 0) TS(0);
    const int b = (tid >> 3) & 31;
    const int2* ipg = reinterpret_cast<const int2*>(idx + (pb0 + b) * NF);
    const int2 i0a = __ldg(ipg), i0b = __ldg(ipg + 16 * NF), i1a = __ldg(ipg + 1), i1b = __ldg(ipg + 16 * NF + 1);
    if (elect_one()) {
        mbar_init(BAR(B_PAIR + warp), warp < 13 ? 256 + (warp == 6) : 1);
        mbar_init(BAR(16 + warp), (warp & 1) ? 9 : 1);
        if (warp >= 13 || warp < NEARLY) {
            asm volatile("fence.mbarrier_init.release.cluster;" ::: "memory");
            mbar_expect_tx(BAR(warp < NEARLY ? B_W + warp : B_PAIR + warp), warp < NEARLY ? HS_BYTES : warp == 13 ? 64 * NF * 4 : 6 * 32 * 4);
            if (warp == 13) bulk_load(sb + OFF_IDX, idx + pb0 * NF, 64 * NF * 4, BAR(B_IDX));
            if (warp < NEARLY) tma_load_3d(sb + OFF_RING + (warp + 2) * HS_BYTES, &tmW1, 0, warp * 64, rank * 2, BAR(B_W + warp));
        }
        if (WPF == 1 && warp == 6) asm volatile("cp.async.bulk.prefetch.L2.global [%0], %1;" ::"l"((const char*)w1 + 4 * 32768 + blockIdx.x * 5632), "n"(5632) : "memory");
        mbar_init(BAR(32 + warp), (warp & 1) ? 9 : 1);
        mbar_init(BAR(48 + warp), 4);
        mbar_init(BAR(64 + warp), warp == B_CDONE - 64 ? 8 : 4);
        mbar_init(BAR(warp), (0x2321 >> (4 * warp)) & 3 | (warp > 3));
        asm volatile("fence.mbarrier_init.release.cluster;" ::: "memory");
    }
    __syncthreads();
    asm volatile("barrier.cluster.arrive.relaxed.aligned;" ::: "memory");
    if (tid == 0) TS(1);

    if (warp >= 12) {
        asm volatile("setmaxnreg.dec.sync.aligned.u32 %0;" ::"n"(R_PROD));
        if (warp == 12) {
#pragma unroll 1
            for (int f = NEARLY; f < NF; f++) {
                if (f >= 4) mbar_wait_bounded(BAR(B_EMPTY + f - 4), 0);
                TSL(80 + f);
                if (elect_one()) {
                    if (WI & 8) mbar_arrive(BAR(B_W + f)); else
                    mbar_expect_tx(BAR(B_W + f), HS_BYTES);
                    if (!(WI & 8))
                    tma_load_3d(sb + OFF_RING + ((f + 2) & 3) * HS_BYTES, &tmW1, 0, f * 64, rank * 2, BAR(B_W + f));

                }
            }
            asm volatile("barrier.cluster.wait.acquire.aligned;" ::: "memory");
            mbar_wait_bounded(BAR(B_FIN), 0);
            float v = 0.f;
#pragma unroll
            for (int i = 0; i < 6; i++) v += __uint_as_float(lds32(sb + OFF_DP + (i * 32 + lane) * 4));
            out[pb0 + 32 * rank + lane] = __float2bfloat16_rn(v);
            TSL(15);
        } else {
            if (warp == 14) {
                if (WPF == 2) {
                    mbar_wait(BAR(B_PAIR), 0);
                    if (elect_one()) asm volatile("cp.async.bulk.prefetch.L2.global [%0], %1;" ::"l"((const char*)w1 + 4 * 32768 + blockIdx.x * 5632), "n"(5632) : "memory");
                }
#pragma unroll 1
                for (int k = 2; k < NF; k++) {
                    mbar_wait(BAR(B_PAIR + min((k + 3) >> 1, 12)), 0);
                    mbar_wait(BAR(B_W + k), 0);
                    asm volatile("bar.arrive %0, 160;" ::"r"(4 + (k & 3)) : "memory");
                }
            } else if (warp == 13) {
                const uint32_t sr = sb + OFF_RT + 16 * RT;
                {
                    uint32_t v[12];
#pragma unroll
                    for (int i = 0; i < 12; i++) v[i] = lane + 32 * (i >> 1) < NF * NFR / 2 ? __ldg(reinterpret_cast<const uint32_t*>((i & 1) ? se_w2 : se_w1) + lane + 32 * (i >> 1)) : 0u;
#pragma unroll
                    for (int i = 0; i < 12; i++) asm volatile("st.shared.u32 [%0], %1;" ::"r"(sr + lane * 4 + (i >> 1) * 128 + (i & 1) * 1024), "r"(v[i]) : "memory");
                    __syncwarp();
                }
#pragma unroll 1
                for (int q = 0; q < 8; q++) {
                    const int c1 = 8 * (q & 1) + g, o1 = c1 < NFR ? min((8 * (q >> 1) + 2 * t) * NFR + c1, NF * NFR) : NF * NFR;
                    const int c2 = 8 * (q & 3) + ((q & 3) < 3 ? 4 * (g & 1) + (g >> 1) : (g & 1)), o2 = min((8 * (q >> 2) + 2 * t) * NF + c2, NF * NFR);
                    uint32_t y1, y2;
                    asm volatile("{\n.reg .b16 a, b, c, d;\nld.shared.b16 a, [%2];\nld.shared.b16 b, [%2 + 26];\nld.shared.b16 c, [%3 + 1024];\nld.shared.b16 d, [%3 + 1076];\n"
                                 "mov.b32 %0, {a, b};\nmov.b32 %1, {c, d};\n}\n" : "=r"(y1), "=r"(y2) : "r"(sr + 2 * o1), "r"(sr + 2 * o2));
                    asm volatile("st.shared.u32 [%0], %1;\nst.shared.u32 [%0 + 1024], %2;" ::"r"(sb + OFF_SEF + q * 128 + lane * 4), "r"(y1),
                                 "r"(hmul2_bf16(y2, 0x3E803E80u))
                                 : "memory");
                }
                fence_proxy_async();
                __syncwarp();
                TSL(12);
                if (elect_one()) mbar_arrive(BAR(B_PAIR + 6));
            } else {
                {
                    const int pq = blockIdx.x >> 6, js = (blockIdx.x >> 1) & 31;
                    const int j = js < 24 ? (js & 24) + 4 * (js & 1) + ((js >> 1) & 3) : 24 + (js & 1);
                    const bool on = js < 24 || ((js >> 1) & 3) == ((lane >> 2) & 3);
                    const __nv_bfloat16* s = w_cross + ((size_t)(pq * NF) * NF + j) * ND + 32 * rank + lane;
                    uint8_t* d = g_wt + (size_t)rank * NCHUNK * CHUNK + (((lane & 15) >> 1) * 2 + (lane >> 4)) * CHUNK + ((lane & 1) * 2 + pq) * TILE + js * 16;
#pragma unroll 1
                    for (int kh = 0; kh < 2; kh++) {
                        uint32_t x[8];
#pragma unroll
                        for (int k = 0; k < 8; k++)
                            x[k] = (on && (kh == 0 || k < 5)) ? ldg_u16(s + (k + (k & 4)) * NF * ND) | (ldg_u16(s + (k == 4 && kh ? 9 : k + (k & 4) + 4) * NF * ND) << 16) : 0u;
                        *reinterpret_cast<uint4*>(d) = make_uint4(x[0], x[1], x[2], x[3]);
                        *reinterpret_cast<uint4*>(d + 512) = make_uint4(x[4], x[5], x[6], x[7]);
                        s += 16 * NF * ND;
                        d += 1024;
                    }
                    __syncwarp();
                }
                TSL(8);
                if (elect_one()) asm volatile("red.release.gpu.global.inc.u32 [%0], %1;" ::"l"(&g_cnt), "n"(NUNIT + 127) : "memory");
                TSL(9);
                mbar_wait(BAR(B_EMPTY + 6), 0);
                TSL(10);
                unsigned int v;
                do {
                    asm volatile("ld.acquire.gpu.global.u32 %0, [%1];" : "=r"(v) : "l"(&g_cnt) : "memory");
                } while (v < NUNIT);
                asm volatile("fence.proxy.async.global;" ::: "memory");
                __syncwarp();
                if (elect_one()) asm volatile("red.relaxed.gpu.global.inc.u32 [%0], %1;" ::"l"(&g_cnt), "n"(NUNIT + 127) : "memory");
                TSL(11);
                const uint8_t* wsrc = g_wt + (size_t)rank * NCHUNK * CHUNK;
#pragma unroll 1
                for (int k = 0; k < 8; k++) {
                    mbar_wait(BAR(B_EMPTY + 20 + ((0x75493260 >> (4 * k)) & 15)), 0);
                    TSL(30 + k);
                    if (elect_one()) {
                        const uint32_t cf = BAR(B_CFULL + ((0x33222110 >> (4 * k)) & 3));
                        mbar_expect_tx(cf, 2 * CHUNK);
                        bulk_load(sb + OFF_TW + ((CPOS >> (4 * k)) & 7) * 2 * CHUNK, wsrc + k * 2 * CHUNK, 2 * CHUNK, cf);
                    }
                }
            }
            __syncwarp();
            asm volatile("barrier.cluster.wait.acquire.aligned;" ::: "memory");
        }
    } else if (warp < 4) {
        {
            const uint4* wb = reinterpret_cast<const uint4*>(w_bi + (tid >> 2) * 64 + 32 * rank + 8 * t);
            const uint4 wb0 = __ldg(wb), wb1 = __ldg(wb + 256);
            const uint32_t w2v = __ldg(reinterpret_cast<const uint32_t*>(w2) + rank * 64 + (tid & 63));
            sts128(sb + OFF_WBI + (tid & 63) * 128 + ((4 ^ (tid & 7)) << 4), 0x3C803C80u, 0x3C803C80u, 0x3C803C80u, 0x3C803C80u);
            asm volatile("st.shared.u32 [%0], %1;" ::"r"(sb + OFF_ID + (tid & 63) * 4), "r"(0x3F803F80u) : "memory");
            asm volatile("st.shared.u32 [%0], %1;" ::"r"(sb + OFF_W2 + (tid & 56) * 4 + (tid & 3) * 8 + (tid & 4)), "r"(w2v) : "memory");
            const uint32_t wd = sb + OFF_WBI + (tid >> 2) * 128 + ((t ^ (g & 7)) << 4);
            sts128(wd, wb0.x, wb0.y, wb0.z, wb0.w);
            sts128(wd + 4096, wb1.x, wb1.y, wb1.z, wb1.w);
            fence_proxy_async();
        }
        asm volatile("setmaxnreg.inc.sync.aligned.u32 %0;" ::"n"(R_DEEP));
        asm volatile("bar.sync 1, 128;" ::: "memory");
        TS(7);
        float acc[64];
        float e2[2][20];
#pragma unroll
        for (int i = 0; i < 64; i++) asm volatile("" : "=f"(acc[i]));
#pragma unroll
        for (int i = 0; i < 20; i++) asm volatile("" : "=f"(e2[0][i]), "=f"(e2[1][i]));
        uint32_t A[4][4][4];
        constexpr uint64_t dr = make_desc(SB0 + OFF_RING, 8192, 1024, 1), dwc = make_desc(SB0 + OFF_WBI, 4096, 1024, 1);
        const uint64_t dw = uni64(dwc + (sb >> 28));
        const uint32_t sa = opq((lane >> 4) * 128 + (2 * warp + ((lane >> 3) & 1)) * 512 + (lane & 7) * 16);
        const uint32_t ln = opq(lane);
        const bool l0 = ln == 0;
        uint32_t la[4];
#pragma unroll
        for (int i = 0; i < 4; i++) la[i] = opq((sb + OFF_RT + (16 * warp + (lane & 15)) * 128 + (((lane >> 4) ^ (lane & 7)) << 4)) ^ (i << 5));
        uint32_t za[8];
#pragma unroll
        for (int i = 0; i < 6; i++) asm volatile("" : "=r"(za[i]));
        auto cvt = [&](uint32_t (&pk)[8], int f) {
            const float(&e)[20] = e2[f & 1];
#pragma unroll
            for (int i = 0; i < 8; i++) asm volatile("cvt.rn.bf16x2.f32 %0, %1, %2;" : "=r"(pk[i]) : "f"(e[2 * i + 1]), "f"(e[2 * i]));
            uint32_t &z0 = za[2 * (f >> 3)], &z1 = za[2 * (f >> 3) + 1];
            asm volatile("{\n.reg .pred p;\nsetp.eq.u32 p, %6, %7;\n@p cvt.rn.bf16x2.f32 %0, %2, %4;\n@p cvt.rn.bf16x2.f32 %1, %3, %5;\n}\n"
                         : "+r"(z0), "+r"(z1)
                         : "f"(e[16]), "f"(e[18]), "f"((f & 1) ? __uint_as_float(z0) : 0.f), "f"((f & 1) ? __uint_as_float(z1) : 0.f), "r"(ln & 3), "r"((f >> 1) & 3));
        };
        auto store = [&](const uint32_t (&pk)[8], int f) {
            stsm_x4_t(sa + sb + OFF_EW + f * EWP, pk[0], pk[1], pk[2], pk[3]);
            stsm_x4_t(sa + sb + OFF_EW + f * EWP + 256, pk[4], pk[5], pk[6], pk[7]);
        };
        auto load1 = [&](auto VC, int i, uint32_t o) {
            constexpr int v = decltype(VC)::value;
            ldsm_x4(la[i ^ (2 * (v & 1))] + o, A[v][i][0], A[v][i][1], A[v][i][2], A[v][i][3]);
        };
        auto mma_e = [&](auto VC) {
            constexpr int v = decltype(VC)::value;
            uint32_t(&ai)[4][4] = A[v];
            wgmma_m64n40k16_rs_tb<2>(e2[v & 1], ai[0], dw);
            wgmma_m64n40k16_rs_tb<1>(e2[v & 1], ai[1], dw + 128);
            wgmma_m64n40k16_rs_tb<1>(e2[v & 1], ai[2], dw + 256);
            wgmma_m64n40k16_rs_tb<1>(e2[v & 1], ai[3], dw + 384);
        };
        auto mma_d1 = [&](auto VC, int i, int sc) {
            constexpr int v = decltype(VC)::value, st = (v + 2) & 3;
            wgmma_m64n128k16_rs_tb(acc, A[v][i], dr + st * (HS_BYTES >> 4) + 128 * i, sc);
        };
        auto mma_d = [&](auto VC, int sc) {
            wgmma_fence();
#pragma unroll
            for (int i = 0; i < 4; i++) mma_d1(VC, i, i ? 1 : sc);
            wgmma_commit();
        };
        auto mma_e1 = [&](auto VC) {
            wgmma_fence();
            mma_e(VC);
            wgmma_commit();
        };
        auto load = [&](auto VC, uint32_t o) {
#pragma unroll
            for (int i = 0; i < 4; i++) load1(VC, i, o);
        };
#define READY(k) asm volatile("bar.sync %0, 160;" ::"n"(4 + ((k) & 3)) : "memory")
        using I0 = std::integral_constant<int, 0>;
        using I1 = std::integral_constant<int, 1>;
        using I2 = std::integral_constant<int, 2>;
        using I3 = std::integral_constant<int, 3>;
        uint32_t pk[8];
        mbar_wait(BAR(B_PAIR), 0);
        TS(19);
        load(I0{}, 0);
        load(I1{}, 6 * RT);
        mma_e1(I0{});
        mbar_wait(BAR(B_W), 0);
        mma_d(I0{}, 0);
        mma_e1(I1{});
        mbar_wait(BAR(B_W + 1), 0);
        mma_d(I1{}, 1);
        mbar_wait(BAR(B_PAIR + 1), 0);
        TS(20);
        load(I2{}, RT);
        load(I3{}, 7 * RT);
        wgmma_wait<2>();
        if (l0) mbar_arrive(BAR(B_EMPTY));
        mbar_wait(BAR(B_PAIR + 2), 0);
        static_for<2, 22>([&](auto KC) {
            constexpr int k = decltype(KC)::value;
            std::integral_constant<int, k & 3> UC;
            cvt(pk, k - 2);
            store(pk, k - 2);
            load(std::integral_constant<int, (k & 3) ^ 2>{}, ((k + 2 + 11 * (k & 1)) / 2) * RT);
            mma_e1(UC);
            READY(k);
            mma_d(UC, 1);
            wgmma_wait<2>();
            if (l0) mbar_arrive(BAR(B_EMPTY + k - 1));
        });
        {
            uint32_t p2[8];
            cvt(pk, 20);
            store(pk, 20);
            load(I0{}, 12 * RT);
            mma_e1(I2{});
            wgmma_wait<2>();
            cvt(pk, 21);
            mma_e1(I3{});
            store(pk, 21);
            READY(22);
            READY(23);
            wgmma_wait<2>();
            if (l0) mbar_arrive(BAR(B_EMPTY + 21));
            load(I1{}, 13 * RT);
            wgmma_wait<1>();
            cvt(pk, 22);
            mma_e1(I0{});
            store(pk, 22);
            wgmma_wait<1>();
            cvt(pk, 23);
            mma_e1(I1{});
            auto mma_h = [&](auto VC, int hh) {
                mma_d1(VC, 2 * hh, 1);
                mma_d1(VC, 2 * hh + 1, 1);
                wgmma_commit();
            };
            mma_h(I2{}, 0);
            store(pk, 23);
            wgmma_wait<1>();
            if (l0) mbar_arrive(BAR(B_ZRDY));
            TS(2);
            za[6] = za[7] = 0u;
            cvt(pk, 24);
            cvt(p2, 25);
#pragma unroll
            for (int i = 0; i < 6; i++) za[i] |= p2[7] & (ln >> 5);
            constexpr uint64_t d1 = make_desc(SB0 + OFF_SEF, 256, 128, 0), d2 = make_desc(SB0 + OFF_SEF + 1024, 512, 128, 0);
            float h[8], o[16];
#pragma unroll
            for (int i = 0; i < 16; i++) asm volatile("" : "=f"(o[i]), "=f"(h[i & 7]));
            wgmma_fence();
            wgmma_m64n16k16_rs<0>(h, za, d1);
            wgmma_m64n16k16_rs<1>(h, za + 4, d1 + 32);
            wgmma_commit();
            mma_h(I2{}, 1);
            mma_d(I3{}, 1);
            wgmma_wait<2>();
            const uint32_t ha0 = pack_bf16(gelu2(h[0]), gelu2(h[1])), ha1 = pack_bf16(gelu2(h[2]), gelu2(h[3])), ha2 = pack_bf16(gelu2(h[4]), gelu2(h[5])),
                           ha3 = pack_bf16(gelu2(h[6]), gelu2(h[7]));
            wgmma_fence();
            wgmma_m64n32k16_rs<2>(o, ha0, ha1, ha2, ha3, d2);
            wgmma_commit();
            wgmma_wait<2>();
            if (l0) mbar_arrive(BAR(B_EMPTY + 22));
            READY(24);
            mma_d(I0{}, 1);
            READY(25);
            store(pk, 24);
            store(p2, 25);
            wgmma_wait<1>();
            if (l0) mbar_arrive(BAR(B_EMPTY + 23));
            mma_d(I1{}, 1);
#pragma unroll
            for (int i = 0; i < 2; i++) {
                uint32_t a[4];
#pragma unroll
                for (int k = 0; k < 4; k++) a[k] = pack_bf16(fmaf(tanh_fast(o[8 * i + 2 * k]), 0.5f, 0.5f), fmaf(tanh_fast(o[8 * i + 2 * k + 1]), 0.5f, 0.5f));
                sts128(sb + OFF_AP + i * 2048 + warp * 512 + ln * 16, a[0], a[1], a[2], a[3]);
            }
            __syncwarp();
            if (l0) mbar_arrive(BAR(B_EWRDY));
            wgmma_wait<1>();
            if (l0) mbar_arrive(BAR(B_EMPTY + 24));
            TS(3);
        }
        {
            wgmma_wait<0>();
            if (l0) mbar_arrive(BAR(B_EMPTY + 25));
            uint32_t hw[32];
#pragma unroll
            for (int i = 0; i < 32; i++) asm volatile("cvt.rn.bf16x2.f32 %0, %1, %2;" : "=r"(hw[i]) : "f"(acc[2 * i + 1]), "f"(acc[2 * i]));
            asm volatile("setmaxnreg.dec.sync.aligned.u32 %0;" ::"n"(R_DEEP2));
            TS(4);
            float o[4] = {0.f, 0.f, 0.f, 0.f};
            int l2;
            asm volatile("mov.u32 %0, %%laneid;" : "=r"(l2));
#pragma unroll
            for (int it = 0; it < 8; it++) {
                uint32_t b0, b1;
                asm volatile("ld.shared.v2.u32 {%0,%1}, [%2];" : "=r"(b0), "=r"(b1) : "r"(sb + OFF_W2 + 8 * (l2 & 3) + it * 32));
                mma16816(o, gelu2p(hw[4 * it]), gelu2p(hw[4 * it + 1]), gelu2p(hw[4 * it + 2]), gelu2p(hw[4 * it + 3]), b0, b1);
            }
            send_partial(sb, rank * 3, warp, l2 >> 2, l2 & 3, 0.5f * o[0], 0.5f * o[2]);
        }
        TS(5);
    } else {
        const int wgc = (warp >> 2) - 1, w4 = warp & 3;
        const char* so = (const char*)table + 16 * (lane & 7);
        auto rp = [&](uint32_t i) { return row_ptr(so, i); };
        const uint32_t d0 = opq(sb + OFF_RT + b * 128 + (((lane ^ b) & 7) << 4)), d1 = opq((d0 ^ 64) + 6 * RT);
        {
            const int ia[4] = {i0a.x, i0a.y, i1a.x, i1a.y}, ib[4] = {i0b.x, i0b.y, i1b.x, i1b.y};
            static_for<0, NFIRST>([&](auto FC) {
                constexpr int f = decltype(FC)::value, o = (f >> 1) * RT;
                cp_async16(((f & 1) ? d1 : d0) + o, rp(ia[f]));
                cp_async16(((f & 1) ? d1 : d0) + o + 4096, rp(ib[f]));
                if (f & 1) cp_async_mbar_arrive_noinc(BAR(B_PAIR + (f >> 1)));
            });
            if (wgc == 0) TS(6);
        }
        asm volatile("setmaxnreg.inc.sync.aligned.u32 %0;" ::"n"(R_CR1));
        uint32_t M[8][12], y[4][2];
        {
            const uint32_t pa = opq(sb + OFF_RT + (t & 1) * 6 * RT + (16 * w4 + g) * 128 + (((4 * rank + 2 * wgc) ^ g ^ (4 * (t & 1))) << 4)), t1 = opq(t >> 1);
            const uint32_t ia = opq(sb + OFF_IDX + b * NF * 4);
#pragma unroll
            for (int i = 0; i < 96; i++) asm volatile("" : "=r"(M[i / 12][i % 12]));
            mbar_wait(BAR(B_IDX), 0);
            uint32_t x[13][4];
#pragma unroll
            for (int p = 2; p < 13; p++)
                asm volatile("ld.shared.v2.u32 {%0,%1}, [%4];\nld.shared.v2.u32 {%2,%3}, [%4 + 3328];" : "=r"(x[p][0]), "=r"(x[p][2]), "=r"(x[p][1]), "=r"(x[p][3]) : "r"(ia + p * 8));
            const uint32_t pb = opq(pa ^ 16);
            auto conv = [&](int G) {
#pragma unroll
                for (int i = 0; i < 16; i++) {
                    uint32_t &u = M[i >> 1][4 * G + 2 * (i & 1)], &v = M[i >> 1][4 * G + 2 * (i & 1) + 1];
                    asm volatile("{\n.reg .b32 t;\nprmt.b32 t, %0, %1, 0x5410;\nprmt.b32 %1, %0, %1, 0x7632;\nmov.b32 %0, t;\n}\n" : "+r"(u), "+r"(v));
                }
#pragma unroll
                for (int i = 0; i < 8; i++)
                    asm volatile("{\n.reg .pred p;\nsetp.eq.u32 p, %5, 2;\n@p st.shared.v4.u32 [%4], {%0,%1,%2,%3};\n}\n" ::"r"(M[i & 4][4 * G + (i & 3)]), "r"(M[(i & 4) + 1][4 * G + (i & 3)]),
                                 "r"(M[(i & 4) + 2][4 * G + (i & 3)]), "r"(M[(i & 4) + 3][4 * G + (i & 3)]), "r"(pa), "r"(t1));
            };
            static_for<0, 15>([&](auto QC) {
                constexpr int q = decltype(QC)::value - 3, p = (int)(GT >> (4 * q + 12)) & 15;
                if (q > 2) mbar_wait(BAR(B_EMPTY + 2 * q - 6), 0);
                if (q > 0) mbar_wait(BAR(B_PAIR + q), 0);
                if (PACE && p == PACE) mbar_wait(BAR(B_PAIR), 0);
                if (p) {
                    constexpr uint32_t o1 = (p < 12 ? p : 7) * RT;
                    cp_async16(d0 + p * RT, rp(x[p][0]));
                    cp_async16(d0 + p * RT + 4096, rp(x[p][1]));
                    cp_async16(d1 + o1, rp(x[p][2]));
                    cp_async16(d1 + o1 + 4096, rp(x[p][3]));
                    cp_async_mbar_arrive_noinc(BAR(B_PAIR + p));
                }
                if (q == 0) mbar_wait(BAR(B_PAIR), 0);
                if constexpr (q >= 0) {
                    constexpr int c = 4 * (q >> 2) + ((q >> 1) & 1);
#pragma unroll
                    for (int i = 0; i < 4; i++)
                        asm volatile("{\n.reg .pred p;\nsetp.eq.u32 p, %5, %6;\n@p ld.shared.v4.u32 {%0,%1,%2,%3}, [%4];\n}\n"
                                     : "+r"(M[2 * (i & 2)][c + 2 * (i & 1)]), "+r"(M[2 * (i & 2) + 1][c + 2 * (i & 1)]), "+r"(M[2 * (i & 2) + 2][c + 2 * (i & 1)]),
                                       "+r"(M[2 * (i & 2) + 3][c + 2 * (i & 1)])
                                     : "r"(((i & 2) ? pb : pa) + q * RT + (i & 1) * 1024), "r"(t1), "n"(q & 1));
                    __syncwarp();
                    if (elect_one()) mbar_arrive(BAR(B_W + 2 * q + 1));
                    if (q == 4 || q == 8) conv(q / 4 - 1);
                }
            });
            const uint32_t ta = sb + OFF_RT + 12 * RT + (16 * w4 + g) * 128 + (((4 * rank + 2 * wgc + (t >> 1)) ^ g) << 4) + 8 * (t & 1);
            mbar_wait(BAR(B_PAIR + 12), 0);
#pragma unroll
            for (int k = 0; k < 4; k++) asm volatile("ld.shared.v2.u32 {%0,%1}, [%2];" : "=r"(y[k][0]), "=r"(y[k][1]) : "r"(((k & 1) ? (ta ^ 64) + RT : ta) + (k >> 1) * 1024));
            __syncwarp();
            if (elect_one()) mbar_arrive(BAR(B_W + 25));
            conv(2);
        }
        uint32_t TL[4][2];
        uint32_t ap[8], a0, a1;
        mbar_wait(BAR(B_CFULL), 0);
        mbar_wait(BAR(B_EWRDY), 0);
        if (wgc == 0) TS(60);
        asm volatile("setmaxnreg.inc.sync.aligned.u32 %0;" ::"n"(R_CR2));
        if (wgc == 0) TS(61);
        {
            int l2;
            asm volatile("mov.u32 %0, %%laneid;" : "=r"(l2));
            const int r = l2 & 7, bh = (l2 >> 3) & 1, ig = l2 >> 4;
            const uint32_t x = sb + OFF_EW + wgc * 256 + (2 * w4 + bh) * 512 + (8 * ig + 4 * (r & 1) + (r >> 1)) * EWP;
            a0 = opq(x);
            a1 = opq(x + (!ig || r == 0 ? 16 : r == 1 ? 13 : 8) * EWP);
#pragma unroll
            for (int i = 0; i < 2; i++) {
                const uint4 v = lds128(sb + OFF_AP + i * 2048 + w4 * 512 + l2 * 16);
                ap[4 * i] = v.x, ap[4 * i + 1] = v.y, ap[4 * i + 2] = v.z, ap[4 * i + 3] = v.w;
            }
        }
        constexpr uint64_t dt = make_desc(SB0 + OFF_TW, 512, 128, 0), dqc = make_desc(SB0 + OFF_ID, 128, 128, 0);
        const uint64_t dq = uni64(dqc + (sb >> 28));
        const uint64_t desc = dt + wgc * (CHUNK >> 4);
        auto dsc = [&](int e, int pq) { return desc + ((CPOS >> (4 * (e >> 1))) & 7) * (2 * CHUNK >> 4) + ((e & 1) * 2 + pq) * (TILE >> 4); };
        float S[4], accP[16], accQ[16];
#pragma unroll
        for (int i = 0; i < 16; i++) asm volatile("" : "=f"(accP[i]), "=f"(accQ[i]));
        uint32_t A0[8], A1[8], Aq[8], w[8];
        u_lda(A0, a0, a1);
        u_lda(A1, a0 + 16, a1 + 16);
#pragma unroll
        for (int k = 0; k < 8; k++) asm volatile("prmt.b32 %0, %1, %2, %3;" : "=r"(TL[k >> 1][k & 1]) : "r"(y[2 * (k & 1)][k >> 2]), "r"(y[2 * (k & 1) + 1][k >> 2]), "r"(0x5410 + 0x2222 * ((k >> 1) & 1)));
#pragma unroll
        for (int i = 0; i < 4; i++) asm volatile("" : "=f"(S[i]));
#pragma unroll
        for (int k = 0; k < 8; k++) Aq[k] = hmul2_bf16(A0[k], ap[k]);
        wgmma_fence();
        u_mma(accP, A0, dsc(0, 0));
        wgmma_commit();
        u_mma(accQ, Aq, dsc(0, 1));
        wgmma_commit();
        if (wgc == 0) TS(62);
        auto pack8 = [&](uint32_t (&d)[8], const float (&a)[16]) {
#pragma unroll
            for (int k = 0; k < 8; k++) asm volatile("cvt.rn.bf16x2.f32 %0, %1, %2;" : "=r"(d[k]) : "f"(a[2 * k + 1]), "f"(a[2 * k]));
        };
        static_for<0, 8>([&](auto PC) {
            constexpr int p = decltype(PC)::value, e = 2 * p;
            auto mw = [&](int s, int k) { return k < 6 ? M[p][2 * k + s] : TL[(e + s) & 3][k - 6]; };
            uint32_t tp[8], tq[8];
            wgmma_wait<1>();
            pack8(tp, accP);
            wgmma_fence();
            u_mma(accP, A1, dsc(e + 1, 0));
            if (p) {
                wgmma_m64n8k16_rs(S, w, dq, p > 1);
                wgmma_m64n8k16_rs(S, w + 4, dq, 1);
            }
            wgmma_commit();
            if (p < 7) u_lda(A0, a0 + 16 * e + 32, a1 + 16 * e + 32);
            wgmma_wait<1>();
            pack8(tq, accQ);
#pragma unroll
            for (int k = 0; k < 8; k++) Aq[k] = hmul2_bf16(A1[k], ap[k]);
            wgmma_fence();
            u_mma(accQ, Aq, dsc(e + 1, 1));
            wgmma_commit();
#pragma unroll
            for (int k = 0; k < 8; k++) tq[k] = hfma2_bf16(tq[k], ap[k], tp[k]);
            if (p == 0 || p == 2 || p == 5) mbar_wait(BAR(B_CFULL + 1 + p / 2), 0);
            wgmma_wait<1>();
            pack8(tp, accP);
            if (p < 7) {
                wgmma_fence();
                u_mma(accP, A0, dsc(e + 2, 0));
                wgmma_commit();
                u_lda(A1, a0 + 16 * e + 48, a1 + 16 * e + 48);
            }
#pragma unroll
            for (int k = 0; k < 8; k++) w[k] = hmul2_bf16(tq[k], mw(0, k));
            wgmma_wait<(p < 7)>();
            if (p == 0 && elect_one()) mbar_arrive(BAR(B_CDONE));
            pack8(tq, accQ);
            if (p < 7) {
#pragma unroll
                for (int k = 0; k < 8; k++) Aq[k] = hmul2_bf16(A0[k], ap[k]);
                wgmma_fence();
                u_mma(accQ, Aq, dsc(e + 2, 1));
                wgmma_commit();
            }
#pragma unroll
            for (int k = 0; k < 8; k++) w[k] = hfma2_bf16(hfma2_bf16(tq[k], ap[k], tp[k]), mw(1, k), w[k]);
        });
        int tid2;
        asm volatile("mov.u32 %0, %%laneid;" : "=r"(tid2));
        wgmma_fence();
        wgmma_m64n8k16_rs(S, w, dq, 1);
        wgmma_m64n8k16_rs(S, w + 4, dq, 1);
        wgmma_commit();
        wgmma_wait<0>();
        send_partial(sb, rank * 3 + 1 + wgc, w4, tid2 >> 2, tid2 & 3, S[0], S[2]);
        if (wgc == 0) TS(14);
    }
#undef BAR
}

typedef CUresult (*PFN_encodeTiled)(CUtensorMap*, CUtensorMapDataType, cuuint32_t, void*, const cuuint64_t*, const cuuint64_t*,
                                    const cuuint32_t*, const cuuint32_t*, CUtensorMapInterleave, CUtensorMapSwizzle,
                                    CUtensorMapL2promotion, CUtensorMapFloatOOBfill);

}

extern "C" void kernel_launch(void* const* d_in, const int* in_sizes, int n_in, void* d_out, int out_size) {
    const int* idx = (const int*)d_in[0];
    const __nv_bfloat16* table = (const __nv_bfloat16*)d_in[1];
    const __nv_bfloat16* se_w1 = (const __nv_bfloat16*)d_in[2];
    const __nv_bfloat16* se_w2 = (const __nv_bfloat16*)d_in[3];
    const __nv_bfloat16* w_bi = (const __nv_bfloat16*)d_in[4];
    const __nv_bfloat16* w_cross = (const __nv_bfloat16*)d_in[5];
    const __nv_bfloat16* w_deep1 = (const __nv_bfloat16*)d_in[6];
    const __nv_bfloat16* w_deep2 = (const __nv_bfloat16*)d_in[7];
    __nv_bfloat16* out = (__nv_bfloat16*)d_out;

    static PFN_encodeTiled enc = nullptr;
    if (!enc) {
        void* fn = nullptr;
        cudaDriverEntryPointQueryResult qres;
        cudaGetDriverEntryPoint("cuTensorMapEncodeTiled", &fn, cudaEnableDefault, &qres);
        enc = (PFN_encodeTiled)fn;
        cudaFuncSetAttribute(fused_kernel, cudaFuncAttributeMaxDynamicSharedMemorySize, SMEM);
    }
    CUtensorMap tm;
    {
        cuuint64_t gdim[3] = {64, (cuuint64_t)(NF * ND), 4};
        cuuint64_t gstr[2] = {(cuuint64_t)NH * 2, 128};
        cuuint32_t box[3] = {64, 64, 2};
        cuuint32_t estr[3] = {1, 1, 1};
        enc(&tm, CU_TENSOR_MAP_DATA_TYPE_BFLOAT16, 3, (void*)w_deep1, gdim, gstr, box, estr, CU_TENSOR_MAP_INTERLEAVE_NONE,
            CU_TENSOR_MAP_SWIZZLE_128B, CU_TENSOR_MAP_L2_PROMOTION_L2_256B, CU_TENSOR_MAP_FLOAT_OOB_FILL_NONE);
    }
    fused_kernel<<<128, 512, SMEM>>>(tm, idx, table, se_w1, se_w2, w_bi, w_cross, w_deep1, w_deep2, out);
}
```

```cpp
#include <cuda_runtime.h>
#include <cuda_bf16.h>
#include <cuda.h>
#include <stdint.h>
#include <type_traits>
#include <utility>

#define R_DEEP 216
#define R_CR1 136
#define R_CR2 216
#define R_DEEP2 56
#define R_PROD 24

namespace {

constexpr int NF = 26, ND = 64, NH = 256, NFR = 13;

#define TS(slot)
#define TSL(slot)

__device__ __forceinline__ uint32_t smem_u32(const void* p) { return (uint32_t)__cvta_generic_to_shared(p); }
__device__ __forceinline__ void mbar_init(uint32_t bar, uint32_t cnt) {
    asm volatile("mbarrier.init.shared::cta.b64 [%0], %1;" ::"r"(bar), "r"(cnt));
}
__device__ __forceinline__ void mbar_expect_tx(uint32_t bar, uint32_t bytes) {
    asm volatile("mbarrier.arrive.expect_tx.shared::cta.b64 _, [%0], %1;" ::"r"(bar), "r"(bytes) : "memory");
}
__device__ __forceinline__ void mbar_arrive(uint32_t bar) {
    asm volatile("mbarrier.arrive.shared::cta.b64 _, [%0];" ::"r"(bar) : "memory");
}
__device__ __forceinline__ void mbar_wait(uint32_t bar, uint32_t parity) {
    asm volatile(
        "{\n"
        ".reg .pred p;\n"
        "WAIT_%=:\n"
        "mbarrier.try_wait.parity.shared::cta.b64 p, [%0], %1;\n"
        "@p bra.uni DONE_%=;\nbra.uni WAIT_%=;\nDONE_%=:\n"
        "}\n" ::"r"(bar),
        "r"(parity)
        : "memory");
}
__device__ __forceinline__ uint32_t opq(uint32_t x) { return __shfl_xor_sync(0xffffffffu, x, 0); }
__device__ __forceinline__ uint64_t uni64(uint64_t x) {
    uint32_t lo = (uint32_t)x, hi = (uint32_t)(x >> 32);
    asm volatile("shfl.sync.idx.b32 %0, %0, 0, 31, -1;\nshfl.sync.idx.b32 %1, %1, 0, 31, -1;" : "+r"(lo), "+r"(hi));
    return ((uint64_t)hi << 32) | lo;
}
__device__ __forceinline__ bool elect_one() {
    uint32_t r;
    asm volatile("{\n.reg .pred p;\nelect.sync _|p, 0xffffffff;\nselp.u32 %0, 1, 0, p;\n}\n" : "=r"(r));
    return r;
}
__device__ __forceinline__ const void* row_ptr(const void* base, uint32_t i) {
    const void* r;
    asm("mad.wide.u32 %0, %1, 128, %2;" : "=l"(r) : "r"(i), "l"(base));
    return r;
}
__device__ __forceinline__ void mbar_wait_bounded(uint32_t bar, uint32_t parity) {
    asm volatile(
        "{\n"
        ".reg .pred p;\n"
        ".reg .u32 c;\n"
        "mov.u32 c, 0;\n"
        "WAIT_%=:\n"
        "mbarrier.try_wait.parity.shared::cta.b64 p, [%0], %1;\n"
        "@p bra.uni DONE_%=;\n"
        "add.u32 c, c, 1;\n"
        "setp.lt.u32 p, c, 0x400000;\n"
        "@p bra.uni WAIT_%=;\n"
        "trap;\n"
        "DONE_%=:\n"
        "}\n" ::"r"(bar),
        "r"(parity)
        : "memory");
}
__device__ __forceinline__ void cp_async16(uint32_t dst, const void* src) {
    asm volatile("cp.async.cg.shared.global [%0], [%1], 16;" ::"r"(dst), "l"(src) : "memory");
}
__device__ __forceinline__ void cp_async_mbar_arrive_noinc(uint32_t bar) {
    asm volatile("cp.async.mbarrier.arrive.noinc.shared::cta.b64 [%0];" ::"r"(bar) : "memory");
}
__device__ __forceinline__ void tma_load_3d(uint32_t dst, const void* tmap, int c0, int c1, int c2, uint32_t bar) {
    asm volatile(
        "cp.async.bulk.tensor.3d.shared::cluster.global.mbarrier::complete_tx::bytes [%0], [%1, {%3, %4, %5}], [%2];" ::"r"(dst),
        "l"(tmap), "r"(bar), "r"(c0), "r"(c1), "r"(c2)
        : "memory");
}
__device__ __forceinline__ void bulk_load(uint32_t dst, const void* src, uint32_t bytes, uint32_t bar) {
    asm volatile("cp.async.bulk.shared::cluster.global.mbarrier::complete_tx::bytes [%0], [%1], %2, [%3];" ::"r"(dst), "l"(src), "r"(bytes),
                 "r"(bar)
                 : "memory");
}
__device__ __forceinline__ void fence_proxy_async() { asm volatile("fence.proxy.async.shared::cta;" ::: "memory"); }
__device__ __forceinline__ void wgmma_fence() { asm volatile("wgmma.fence.sync.aligned;" ::: "memory"); }
__device__ __forceinline__ void wgmma_commit() { asm volatile("wgmma.commit_group.sync.aligned;" ::: "memory"); }
template <int N> __device__ __forceinline__ void wgmma_wait() { asm volatile("wgmma.wait_group.sync.aligned %0;" ::"n"(N) : "memory"); }

__device__ __forceinline__ void ldsm_x4(uint32_t addr, uint32_t& r0, uint32_t& r1, uint32_t& r2, uint32_t& r3) {
    asm volatile("ldmatrix.sync.aligned.m8n8.x4.shared.b16 {%0,%1,%2,%3}, [%4];" : "=r"(r0), "=r"(r1), "=r"(r2), "=r"(r3) : "r"(addr));
}
__device__ __forceinline__ void ldsm_x4_t(uint32_t addr, uint32_t& r0, uint32_t& r1, uint32_t& r2, uint32_t& r3) {
    asm volatile("ldmatrix.sync.aligned.m8n8.x4.trans.shared.b16 {%0,%1,%2,%3}, [%4];" : "=r"(r0), "=r"(r1), "=r"(r2), "=r"(r3) : "r"(addr));
}
__device__ __forceinline__ void stsm_x4_t(uint32_t addr, uint32_t r0, uint32_t r1, uint32_t r2, uint32_t r3) {
    asm volatile("stmatrix.sync.aligned.m8n8.x4.trans.shared.b16 [%0], {%1,%2,%3,%4};" ::"r"(addr), "r"(r0), "r"(r1), "r"(r2), "r"(r3) : "memory");
}
__device__ __forceinline__ uint4 lds128(uint32_t addr) {
    uint4 v;
    asm volatile("ld.shared.v4.u32 {%0,%1,%2,%3}, [%4];" : "=r"(v.x), "=r"(v.y), "=r"(v.z), "=r"(v.w) : "r"(addr));
    return v;
}
__device__ __forceinline__ uint32_t lds32(uint32_t addr) {
    uint32_t v;
    asm volatile("ld.shared.u32 %0, [%1];" : "=r"(v) : "r"(addr));
    return v;
}
__device__ __forceinline__ void sts128(uint32_t addr, uint32_t a, uint32_t b, uint32_t c, uint32_t d) {
    asm volatile("st.shared.v4.u32 [%0], {%1,%2,%3,%4};" ::"r"(addr), "r"(a), "r"(b), "r"(c), "r"(d) : "memory");
}
__device__ __forceinline__ void mma16816(float (&c)[4], uint32_t a0, uint32_t a1, uint32_t a2, uint32_t a3, uint32_t b0, uint32_t b1) {
    asm("mma.sync.aligned.m16n8k16.row.col.f32.bf16.bf16.f32 {%0,%1,%2,%3}, {%4,%5,%6,%7}, {%8,%9}, {%0,%1,%2,%3};"
        : "+f"(c[0]), "+f"(c[1]), "+f"(c[2]), "+f"(c[3])
        : "r"(a0), "r"(a1), "r"(a2), "r"(a3), "r"(b0), "r"(b1));
}
__device__ __forceinline__ uint32_t pack_bf16(float lo, float hi) {
    uint32_t r;
    asm("cvt.rn.bf16x2.f32 %0, %1, %2;" : "=r"(r) : "f"(hi), "f"(lo));
    return r;
}
__device__ __forceinline__ uint32_t hmul2_bf16(uint32_t a, uint32_t b) {
    uint32_t r;
    asm("mul.rn.bf16x2 %0, %1, %2;" : "=r"(r) : "r"(a), "r"(b));
    return r;
}
__device__ __forceinline__ float tanh_fast(float x) {
    float r;
    asm("tanh.approx.f32 %0, %1;" : "=f"(r) : "f"(x));
    return r;
}
#define WG_ACC8(c, b) c(acc[b]), c(acc[b + 1]), c(acc[b + 2]), c(acc[b + 3]), c(acc[b + 4]), c(acc[b + 5]), c(acc[b + 6]), c(acc[b + 7])
#define WG_N128(c, sc)                                                                                                              \
    asm volatile(                                                                                                                   \
        "{\n"                                                                                                                       \
        ".reg .pred p;\n"                                                              \
        "setp.ne.b32 p, " sc ", 0;\n"                                                                                               \
        "wgmma.mma_async.sync.aligned.m64n128k16.f32.bf16.bf16 "                                                                    \
        "{%0,%1,%2,%3,%4,%5,%6,%7,%8,%9,%10,%11,%12,%13,%14,%15,"                                                                   \
        "%16,%17,%18,%19,%20,%21,%22,%23,%24,%25,%26,%27,%28,%29,%30,%31,"                                                          \
        "%32,%33,%34,%35,%36,%37,%38,%39,%40,%41,%42,%43,%44,%45,%46,%47,"                                                          \
        "%48,%49,%50,%51,%52,%53,%54,%55,%56,%57,%58,%59,%60,%61,%62,%63},"                                                         \
        " {%64,%65,%66,%67}, %68, p, 1, 1, 1;\n"                                                                                    \
        "}\n"                                                                                                                       \
        : WG_ACC8(c, 0), WG_ACC8(c, 8), WG_ACC8(c, 16), WG_ACC8(c, 24), WG_ACC8(c, 32), WG_ACC8(c, 40), WG_ACC8(c, 48), WG_ACC8(c, 56) \
        : "r"(a[0]), "r"(a[1]), "r"(a[2]), "r"(a[3]), "l"(db), "r"(scv))
__device__ __forceinline__ void wgmma_m64n128k16_rs_tb(float (&acc)[64], const uint32_t (&a)[4], uint64_t db, int scv) {
    WG_N128("+f", "%69");
}
#define WG_N40(c, sc)                                                                         \
    asm volatile(                                                                             \
        "{\n"                                                                                 \
        ".reg .pred p;\n"                        \
        "setp.ne.b32 p, " sc ", 0;\n"                                                         \
        "wgmma.mma_async.sync.aligned.m64n40k16.f32.bf16.bf16 "                               \
        "{%0,%1,%2,%3,%4,%5,%6,%7,%8,%9,%10,%11,%12,%13,%14,%15,%16,%17,%18,%19},"            \
        " {%20,%21,%22,%23}, %24, p, 1, 1, 1;\n"                                              \
        "}\n"                                                                                 \
        : WG_ACC8(c, 0), WG_ACC8(c, 8), c(acc[16]), c(acc[17]), c(acc[18]), c(acc[19])        \
        : "r"(a[0]), "r"(a[1]), "r"(a[2]), "r"(a[3]), "l"(db))
template <int SC>
__device__ __forceinline__ void wgmma_m64n40k16_rs_tb(float (&acc)[20], const uint32_t (&a)[4], uint64_t db) {
    if constexpr (SC == 1) WG_N40("+f", "1");
    else if constexpr (SC == 2) WG_N40("+f", "0");
    else WG_N40("=f", "0");
}
#define WG_N32(c, sc)                                                   \
    asm volatile(                                                       \
        "{\n"                                                           \
        ".reg .pred p;\n"           \
        "setp.ne.b32 p, " sc ", 0;\n"                                   \
        "wgmma.mma_async.sync.aligned.m64n32k16.f32.bf16.bf16 "         \
        "{%0,%1,%2,%3,%4,%5,%6,%7,%8,%9,%10,%11,%12,%13,%14,%15},"      \
        " {%16,%17,%18,%19}, %20, p, 1, 1, 0;\n"                        \
        "}\n"                                                           \
        : WG_ACC8(c, 0), WG_ACC8(c, 8)                                  \
        : "r"(a0), "r"(a1), "r"(a2), "r"(a3), "l"(db))
template <int SC>
__device__ __forceinline__ void wgmma_m64n32k16_rs(float (&acc)[16], uint32_t a0, uint32_t a1, uint32_t a2, uint32_t a3, uint64_t db) {
    if constexpr (SC == 1) WG_N32("+f", "1");
    else if constexpr (SC == 2) WG_N32("+f", "0");
    else WG_N32("=f", "0");
}

__host__ __device__ constexpr uint64_t make_desc(uint32_t addr, uint32_t lbo_bytes, uint32_t sbo_bytes, uint32_t swz) {
    uint64_t d = 0;
    d |= (uint64_t)((addr & 0x3FFFF) >> 4);
    d |= (uint64_t)((lbo_bytes >> 4) & 0x3FFF) << 16;
    d |= (uint64_t)((sbo_bytes >> 4) & 0x3FFF) << 32;
    d |= (uint64_t)swz << 62;
    return d;
}
__device__ __forceinline__ uint32_t ldg_u16(const __nv_bfloat16* p) { return (uint32_t)__ldg(reinterpret_cast<const unsigned short*>(p)); }
template <int N, class F, int... I>
__device__ __forceinline__ void static_for_impl(F&& f, std::integer_sequence<int, I...>) {
    (f(std::integral_constant<int, N + I>{}), ...);
}
template <int B, int E, class F>
__device__ __forceinline__ void static_for(F&& f) {
    static_for_impl<B>(f, std::make_integer_sequence<int, E - B>{});
}

__device__ __forceinline__ uint32_t hfma2_bf16(uint32_t a, uint32_t b, uint32_t c) {
    uint32_t r;
    asm("fma.rn.bf16x2 %0, %1, %2, %3;" : "=r"(r) : "r"(a), "r"(b), "r"(c));
    return r;
}
__device__ __forceinline__ float gelu2(float x) {
    const float k0 = 0.7978845608028654f, k01 = 0.7978845608028654f * 0.044715f;
    return fmaf(x, tanh_fast(x * fmaf(x * x, k01, k0)), x);
}
__device__ __forceinline__ uint32_t gelu2p(uint32_t x) {
    uint32_t t;
    const uint32_t u = hmul2_bf16(x, hfma2_bf16(hmul2_bf16(x, x), 0x3D123D12u, 0x3F4C3F4Cu));
    asm("tanh.approx.bf16x2 %0, %1;" : "=r"(t) : "r"(u));
    return hfma2_bf16(x, t, x);
}
__device__ __forceinline__ void wgmma_m64n8k16_rs(float (&acc)[4], const uint32_t* a, uint64_t db, int sc) {
    asm volatile("{\n.reg .pred p;\nsetp.ne.b32 p, %9, 0;\nwgmma.mma_async.sync.aligned.m64n8k16.f32.bf16.bf16 {%0,%1,%2,%3}, {%4,%5,%6,%7}, %8, p, 1, 1, 0;\n}\n"
                 : "+f"(acc[0]), "+f"(acc[1]), "+f"(acc[2]), "+f"(acc[3])
                 : "r"(a[0]), "r"(a[1]), "r"(a[2]), "r"(a[3]), "l"(db), "r"(sc));
}

template <int SC>
__device__ __forceinline__ void wgmma_m64n16k16_rs(float (&acc)[8], const uint32_t* a, uint64_t db) {
    asm volatile("{\n.reg .pred p;\nsetp.ne.b32 p, %13, 0;\nwgmma.mma_async.sync.aligned.m64n16k16.f32.bf16.bf16 {%0,%1,%2,%3,%4,%5,%6,%7}, {%8,%9,%10,%11}, %12, p, 1, 1, 0;\n}\n"
                 : WG_ACC8("+f", 0)
                 : "r"(a[0]), "r"(a[1]), "r"(a[2]), "r"(a[3]), "l"(db), "n"(SC));
}

constexpr int SB0 = 1024;
constexpr int SLOT = 4096;
constexpr int EWP = SLOT + 16;
constexpr int OFF_EW = 608;
constexpr int OFF_RT = 1024;
constexpr int RT = 8192;
constexpr int OFF_TW = OFF_RT + 13 * RT;
constexpr int HS_BYTES = 16384;
constexpr int OFF_RING = OFF_RT + 19 * RT;
constexpr int OFF_WBI = OFF_RT + 18 * RT;
constexpr int OFF_IDX = OFF_RT + 17 * RT;
constexpr int OFF_SEF = OFF_RING + 4 * HS_BYTES;
constexpr int OFF_AP = OFF_SEF + 2048;
constexpr int OFF_W2 = 0;
constexpr int OFF_DP = OFF_AP + 4096;
constexpr int OFF_ID = OFF_DP + 6 * 32 * 4;
constexpr int OFF_BAR = OFF_ID + 256;
constexpr int TILE = 2048;
constexpr int CHUNK = 4 * TILE;
constexpr int NCHUNK = 16;
constexpr int CPOS = 0x16504321;
static_assert(OFF_TW + 14 * CHUNK == OFF_SEF && OFF_EW + 25 * EWP + SLOT <= OFF_TW, "layout");
static_assert(OFF_RING % 1024 == 0 && OFF_WBI % 1024 == 0 && OFF_ID % 128 == 0, "align");
constexpr int B_CFULL = 0,
              B_W = 16,
              B_EMPTY = 48, B_ZRDY = B_EMPTY + NF, B_CDONE = B_ZRDY + 1,
              B_EWRDY = B_CDONE + 2, B_PAIR = 80,
              B_IDX = B_PAIR + 13, B_FIN = B_PAIR + 14;
constexpr int OFF_TS = OFF_BAR + 768;
constexpr int SMEM = OFF_TS + 512;
static_assert(SMEM <= 232448, "smem");
constexpr int NFIRST = 4;
constexpr int NUNIT = 128;

__device__ __align__(1024) uint8_t g_wt[2 * NCHUNK * CHUNK];
__device__ unsigned int g_cnt;

__device__ __forceinline__ void u_lda(uint32_t (&A)[8], uint32_t a0, uint32_t a1) {
    ldsm_x4_t(a0, A[0], A[1], A[2], A[3]);
    ldsm_x4_t(a1, A[4], A[5], A[6], A[7]);
}
__device__ __forceinline__ void u_mma(float (&acc)[16], const uint32_t (&A)[8], uint64_t desc) {
    wgmma_m64n32k16_rs<2>(acc, A[0], A[1], A[2], A[3], desc);
    wgmma_m64n32k16_rs<1>(acc, A[4], A[5], A[6], A[7], desc + 64);
}
__device__ __forceinline__ void send_partial(uint32_t sb, int src, int w4, int g, int t, float v0, float v1) {
    asm volatile("barrier.cluster.wait.acquire.aligned;" ::: "memory");
    if (t < 2) {
        uint32_t rb;
        asm volatile("mapa.shared::cluster.u32 %0, %1, %2;" : "=r"(rb) : "r"(sb), "r"(w4 >> 1));
        asm volatile("st.async.weak.shared::cluster.mbarrier::complete_tx::bytes.f32 [%0], %1, [%2];" ::"r"(rb + OFF_DP + (src * 32 + (w4 & 1) * 16 + 8 * t + g) * 4),
                     "f"(t ? v1 : v0), "r"(rb + OFF_BAR + B_FIN * 8)
                     : "memory");
    }
}

__global__ void __cluster_dims__(2, 1, 1) __launch_bounds__(512, 1)
fused_kernel(const int* __restrict__ idx, const __nv_bfloat16* __restrict__ table, const __nv_bfloat16* __restrict__ w1, const __nv_bfloat16* __restrict__ w_bi,
             const __nv_bfloat16* __restrict__ w2, const __nv_bfloat16* __restrict__ w_cross, const __nv_bfloat16* __restrict__ se_w1,
             const __nv_bfloat16* __restrict__ se_w2, __nv_bfloat16* __restrict__ out, const __grid_constant__ CUtensorMap tmW1) {
    extern __shared__ __align__(1024) uint8_t smem_raw[];
    const int tid = threadIdx.x, b = (tid >> 3) & 31;
    const int pb0 = (blockIdx.x >> 1) * 64;
    int2 i0a, i0b, i1a, i1b;
    asm volatile("ld.global.nc.v2.u32 {%0,%1}, [%8];\nld.global.nc.v2.u32 {%2,%3}, [%8 + 3328];\nld.global.nc.v2.u32 {%4,%5}, [%8 + 8];\nld.global.nc.v2.u32 {%6,%7}, [%8 + 3336];"
                 : "=r"(i0a.x), "=r"(i0a.y), "=r"(i0b.x), "=r"(i0b.y), "=r"(i1a.x), "=r"(i1a.y), "=r"(i1b.x), "=r"(i1b.y)
                 : "l"(idx + (pb0 + b) * NF));
    const uint32_t sb = __shfl_sync(0xffffffffu, smem_u32(smem_raw), 0);
    const uint32_t bars = sb + OFF_BAR;
#define BAR(i) (bars + (i) * 8)
    const int warp = __shfl_sync(0xffffffffu, tid >> 5, 0), lane = tid & 31, g = lane >> 2, t = lane & 3;
    const int rank = blockIdx.x & 1;
    if (tid == 0) TS(0);
    if (elect_one()) {
        mbar_init(BAR(B_PAIR + warp), warp < 13 ? 256 + (warp == 10) : 1);
        if (warp >= 13) {
            asm volatile("fence.mbarrier_init.release.cluster;" ::: "memory");
            mbar_expect_tx(BAR(B_PAIR + warp), warp == 13 ? 64 * NF * 4 : 6 * 32 * 4);
            if (warp == 13) bulk_load(sb + OFF_IDX, idx + pb0 * NF, 64 * NF * 4, BAR(B_IDX));
        }
        if (warp == 6) asm volatile("cp.async.bulk.prefetch.L2.global [%0], %1;" ::"l"((const char*)w1 + 4 * 32768 + blockIdx.x * 5632), "n"(5632) : "memory");
        mbar_init(BAR(16 + warp), (warp & 1) ? 9 : 1);
        mbar_init(BAR(32 + warp), (warp & 1) ? 9 : 1);
        mbar_init(BAR(48 + warp), 4);
        mbar_init(BAR(64 + warp), warp == B_CDONE - 64 ? 8 : 4);
        if (warp < 4) mbar_init(BAR(warp), (0x2321 >> (4 * warp)) & 3);
        asm volatile("fence.mbarrier_init.release.cluster;" ::: "memory");
    }
    __syncthreads();
    asm volatile("barrier.cluster.arrive.relaxed.aligned;" ::: "memory");
    if (tid == 0) TS(1);

    if (warp >= 12) {
        asm volatile("setmaxnreg.dec.sync.aligned.u32 %0;" ::"n"(R_PROD));
        if ((sb & 0xFFFFFFu) != SB0) __trap();
        if (warp == 12) {
#pragma unroll 1
            for (int f = 0; f < NF; f++) {
                if (f >= 4) mbar_wait_bounded(BAR(B_EMPTY + f - 4), 0);
                TSL(80 + f);
                if (elect_one()) {
                    mbar_expect_tx(BAR(B_W + f), HS_BYTES);
                    tma_load_3d(sb + OFF_RING + ((f + 2) & 3) * HS_BYTES, &tmW1, 0, f * 64, rank * 2, BAR(B_W + f));
                }
            }
            asm volatile("barrier.cluster.wait.acquire.aligned;" ::: "memory");
            mbar_wait_bounded(BAR(B_FIN), 0);
            float v = 0.f;
#pragma unroll
            for (int i = 0; i < 6; i++) v += __uint_as_float(lds32(sb + OFF_DP + (i * 32 + lane) * 4));
            out[pb0 + 32 * rank + lane] = __float2bfloat16_rn(v);
            TSL(15);
        } else {
            if (warp == 14) {
#pragma unroll 1
                for (int k = 2; k < NF; k++) {
                    mbar_wait(BAR(B_PAIR + min((k + 3) >> 1, 12)), 0);
                    mbar_wait(BAR(B_W + k), 0);
                    asm volatile("bar.arrive %0, 160;" ::"r"(4 + (k & 3)) : "memory");
                }
            } else if (warp == 13) {
                const uint32_t sr = sb + OFF_AP;
                {
                    uint32_t v[12];
#pragma unroll
                    for (int i = 0; i < 12; i++) v[i] = lane + 32 * (i >> 1) < NF * NFR / 2 ? __ldg(reinterpret_cast<const uint32_t*>((i & 1) ? se_w2 : se_w1) + lane + 32 * (i >> 1)) : 0u;
#pragma unroll
                    for (int i = 0; i < 12; i++) asm volatile("st.shared.u32 [%0], %1;" ::"r"(sr + lane * 4 + (i >> 1) * 128 + (i & 1) * 1024), "r"(v[i]) : "memory");
                    __syncwarp();
                }
#pragma unroll 1
                for (int q = 0; q < 8; q++) {
                    const int c1 = 8 * (q & 1) + g, o1 = c1 < NFR ? min((8 * (q >> 1) + 2 * t) * NFR + c1, NF * NFR) : NF * NFR;
                    const int c2 = 8 * (q & 3) + ((q & 3) < 3 ? 4 * (g & 1) + (g >> 1) : (g & 1)), o2 = min((8 * (q >> 2) + 2 * t) * NF + c2, NF * NFR);
                    uint32_t y1, y2;
                    asm volatile("{\n.reg .b16 a, b, c, d;\nld.shared.b16 a, [%2];\nld.shared.b16 b, [%2 + 26];\nld.shared.b16 c, [%3 + 1024];\nld.shared.b16 d, [%3 + 1076];\n"
                                 "mov.b32 %0, {a, b};\nmov.b32 %1, {c, d};\n}\n" : "=r"(y1), "=r"(y2) : "r"(sr + 2 * o1), "r"(sr + 2 * o2));
                    asm volatile("st.shared.u32 [%0], %1;\nst.shared.u32 [%0 + 1024], %2;" ::"r"(sb + OFF_SEF + q * 128 + lane * 4), "r"(y1),
                                 "r"(hmul2_bf16(y2, 0x3E803E80u))
                                 : "memory");
                }
                fence_proxy_async();
                __syncwarp();
                TSL(12);
                if (elect_one()) mbar_arrive(BAR(B_PAIR + 10));
            } else {
                {
                    const int pq = blockIdx.x >> 6, js = (blockIdx.x >> 1) & 31;
                    const int j = js < 24 ? (js & 24) + 4 * (js & 1) + ((js >> 1) & 3) : 24 + (js & 1);
                    const bool on = js < 24 || ((js >> 1) & 3) == ((lane >> 2) & 3);
                    const __nv_bfloat16* s = w_cross + ((size_t)(pq * NF) * NF + j) * ND + 32 * rank + lane;
                    uint8_t* d = g_wt + (size_t)rank * NCHUNK * CHUNK + (((lane & 15) >> 1) * 2 + (lane >> 4)) * CHUNK + ((lane & 1) * 2 + pq) * TILE + js * 16;
#pragma unroll 1
                    for (int kh = 0; kh < 2; kh++) {
                        uint32_t x[8];
#pragma unroll
                        for (int k = 0; k < 8; k++)
                            x[k] = (on && (kh == 0 || k < 5)) ? ldg_u16(s + (k + (k & 4)) * NF * ND) | (ldg_u16(s + (k == 4 && kh ? 9 : k + (k & 4) + 4) * NF * ND) << 16) : 0u;
                        *reinterpret_cast<uint4*>(d) = make_uint4(x[0], x[1], x[2], x[3]);
                        *reinterpret_cast<uint4*>(d + 512) = make_uint4(x[4], x[5], x[6], x[7]);
                        s += 16 * NF * ND;
                        d += 1024;
                    }
                    __syncwarp();
                }
                TSL(8);
                if (elect_one()) asm volatile("red.release.gpu.global.inc.u32 [%0], %1;" ::"l"(&g_cnt), "n"(NUNIT + 127) : "memory");
                TSL(9);
                mbar_wait(BAR(B_EMPTY + 6), 0);
                TSL(10);
                unsigned int v;
                do {
                    asm volatile("ld.acquire.gpu.global.u32 %0, [%1];" : "=r"(v) : "l"(&g_cnt) : "memory");
                } while (v < NUNIT);
                asm volatile("fence.proxy.async.global;" ::: "memory");
                __syncwarp();
                if (elect_one()) asm volatile("red.relaxed.gpu.global.inc.u32 [%0], %1;" ::"l"(&g_cnt), "n"(NUNIT + 127) : "memory");
                TSL(11);
                const uint8_t* wsrc = g_wt + (size_t)rank * NCHUNK * CHUNK;
#pragma unroll 1
                for (int k = 0; k < 8; k++) {
                    mbar_wait(BAR(B_EMPTY + 20 + ((0x75493260 >> (4 * k)) & 15)), 0);
                    TSL(30 + k);
                    if (elect_one()) {
                        const uint32_t cf = BAR(B_CFULL + ((0x33222110 >> (4 * k)) & 3));
                        mbar_expect_tx(cf, 2 * CHUNK);
                        bulk_load(sb + OFF_TW + ((CPOS >> (4 * k)) & 7) * 2 * CHUNK, wsrc + k * 2 * CHUNK, 2 * CHUNK, cf);
                    }
                }
            }
            __syncwarp();
            asm volatile("barrier.cluster.wait.acquire.aligned;" ::: "memory");
        }
    } else if (warp < 4) {
        {
            const uint4* wb = reinterpret_cast<const uint4*>(w_bi + (tid >> 2) * 64 + 32 * rank + 8 * t);
            const uint4 wb0 = __ldg(wb), wb1 = __ldg(wb + 256);
            const uint32_t w2v = __ldg(reinterpret_cast<const uint32_t*>(w2) + rank * 64 + (tid & 63));
            sts128(sb + OFF_WBI + (tid & 63) * 128 + ((4 ^ (tid & 7)) << 4), 0x3C803C80u, 0x3C803C80u, 0x3C803C80u, 0x3C803C80u);
            asm volatile("st.shared.u32 [%0], %1;" ::"r"(sb + OFF_ID + (tid & 63) * 4), "r"(0x3F803F80u) : "memory");
            asm volatile("st.shared.u32 [%0], %1;" ::"r"(sb + OFF_W2 + (tid & 56) * 4 + (tid & 3) * 8 + (tid & 4)), "r"(w2v) : "memory");
            const uint32_t wd = sb + OFF_WBI + (tid >> 2) * 128 + ((t ^ (g & 7)) << 4);
            sts128(wd, wb0.x, wb0.y, wb0.z, wb0.w);
            sts128(wd + 4096, wb1.x, wb1.y, wb1.z, wb1.w);
            fence_proxy_async();
        }
        asm volatile("setmaxnreg.inc.sync.aligned.u32 %0;" ::"n"(R_DEEP));
        asm volatile("bar.sync 1, 128;" ::: "memory");
        TS(7);
        float acc[64];
        float e2[2][20];
#pragma unroll
        for (int i = 0; i < 64; i++) asm volatile("" : "=f"(acc[i]));
#pragma unroll
        for (int i = 0; i < 20; i++) asm volatile("" : "=f"(e2[0][i]), "=f"(e2[1][i]));
        uint32_t A[4][4][4];
        constexpr uint64_t dr = make_desc(SB0 + OFF_RING, 8192, 1024, 1), dwc = make_desc(SB0 + OFF_WBI, 4096, 1024, 1);
        const uint64_t dw = uni64(dwc + (sb >> 28));
        const uint32_t sa = opq((lane >> 4) * 128 + (2 * warp + ((lane >> 3) & 1)) * 512 + (lane & 7) * 16);
        const uint32_t ln = opq(lane);
        const bool l0 = ln == 0;
        uint32_t la[4];
#pragma unroll
        for (int i = 0; i < 4; i++) la[i] = opq((sb + OFF_RT + (16 * warp + (lane & 15)) * 128 + (((lane >> 4) ^ (lane & 7)) << 4)) ^ (i << 5));
        uint32_t za[8];
#pragma unroll
        for (int i = 0; i < 6; i++) asm volatile("" : "=r"(za[i]));
        auto cvt = [&](uint32_t (&pk)[8], int f) {
            const float(&e)[20] = e2[f & 1];
#pragma unroll
            for (int i = 0; i < 8; i++) asm volatile("cvt.rn.bf16x2.f32 %0, %1, %2;" : "=r"(pk[i]) : "f"(e[2 * i + 1]), "f"(e[2 * i]));
            uint32_t &z0 = za[2 * (f >> 3)], &z1 = za[2 * (f >> 3) + 1];
            asm volatile("{\n.reg .pred p;\nsetp.eq.u32 p, %6, %7;\n@p cvt.rn.bf16x2.f32 %0, %2, %4;\n@p cvt.rn.bf16x2.f32 %1, %3, %5;\n}\n"
                         : "+r"(z0), "+r"(z1)
                         : "f"(e[16]), "f"(e[18]), "f"((f & 1) ? __uint_as_float(z0) : 0.f), "f"((f & 1) ? __uint_as_float(z1) : 0.f), "r"(ln & 3), "r"((f >> 1) & 3));
        };
        auto store = [&](const uint32_t (&pk)[8], int f) {
            stsm_x4_t(sa + sb + OFF_EW + f * EWP, pk[0], pk[1], pk[2], pk[3]);
            stsm_x4_t(sa + sb + OFF_EW + f * EWP + 256, pk[4], pk[5], pk[6], pk[7]);
        };
        auto load1 = [&](auto VC, int i, uint32_t o) {
            constexpr int v = decltype(VC)::value;
            ldsm_x4(la[i ^ (2 * (v & 1))] + o, A[v][i][0], A[v][i][1], A[v][i][2], A[v][i][3]);
        };
        auto mma_e = [&](auto VC) {
            constexpr int v = decltype(VC)::value;
            uint32_t(&ai)[4][4] = A[v];
            wgmma_m64n40k16_rs_tb<2>(e2[v & 1], ai[0], dw);
            wgmma_m64n40k16_rs_tb<1>(e2[v & 1], ai[1], dw + 128);
            wgmma_m64n40k16_rs_tb<1>(e2[v & 1], ai[2], dw + 256);
            wgmma_m64n40k16_rs_tb<1>(e2[v & 1], ai[3], dw + 384);
        };
        auto mma_d1 = [&](auto VC, int i, int sc) {
            constexpr int v = decltype(VC)::value, st = (v + 2) & 3;
            wgmma_m64n128k16_rs_tb(acc, A[v][i], dr + st * (HS_BYTES >> 4) + 128 * i, sc);
        };
        auto mma_d = [&](auto VC, int sc) {
            wgmma_fence();
#pragma unroll
            for (int i = 0; i < 4; i++) mma_d1(VC, i, i ? 1 : sc);
            wgmma_commit();
        };
        auto mma_e1 = [&](auto VC) {
            wgmma_fence();
            mma_e(VC);
            wgmma_commit();
        };
        auto load = [&](auto VC, uint32_t o) {
#pragma unroll
            for (int i = 0; i < 4; i++) load1(VC, i, o);
        };
#define READY(k) asm volatile("bar.sync %0, 160;" ::"n"(4 + ((k) & 3)) : "memory")
        using I0 = std::integral_constant<int, 0>;
        using I1 = std::integral_constant<int, 1>;
        using I2 = std::integral_constant<int, 2>;
        using I3 = std::integral_constant<int, 3>;
        uint32_t pk[8];
        mbar_wait(BAR(B_PAIR), 0);
        TS(19);
        load(I0{}, 0);
        load(I1{}, 6 * RT);
        mma_e1(I0{});
        mbar_wait(BAR(B_W), 0);
        mma_d(I0{}, 0);
        mma_e1(I1{});
        mbar_wait(BAR(B_W + 1), 0);
        mma_d(I1{}, 1);
        mbar_wait(BAR(B_PAIR + 1), 0);
        TS(20);
        load(I2{}, RT);
        load(I3{}, 7 * RT);
        wgmma_wait<2>();
        if (l0) mbar_arrive(BAR(B_EMPTY));
        mbar_wait(BAR(B_PAIR + 2), 0);
        static_for<2, 22>([&](auto KC) {
            constexpr int k = decltype(KC)::value;
            std::integral_constant<int, k & 3> UC;
            cvt(pk, k - 2);
            store(pk, k - 2);
            load(std::integral_constant<int, (k & 3) ^ 2>{}, ((k + 2 + 11 * (k & 1)) / 2) * RT);
            mma_e1(UC);
            READY(k);
            mma_d(UC, 1);
            wgmma_wait<2>();
            if (l0) mbar_arrive(BAR(B_EMPTY + k - 1));
        });
        {
            uint32_t p2[8];
            cvt(pk, 20);
            store(pk, 20);
            load(I0{}, 12 * RT);
            mma_e1(I2{});
            wgmma_wait<2>();
            cvt(pk, 21);
            mma_e1(I3{});
            store(pk, 21);
            READY(22);
            READY(23);
            wgmma_wait<2>();
            if (l0) mbar_arrive(BAR(B_EMPTY + 21));
            load(I1{}, 13 * RT);
            wgmma_wait<1>();
            cvt(pk, 22);
            mma_e1(I0{});
            store(pk, 22);
            wgmma_wait<1>();
            cvt(pk, 23);
            mma_e1(I1{});
            auto mma_h = [&](auto VC, int hh) {
                mma_d1(VC, 2 * hh, 1);
                mma_d1(VC, 2 * hh + 1, 1);
                wgmma_commit();
            };
            mma_h(I2{}, 0);
            store(pk, 23);
            wgmma_wait<1>();
            if (l0) mbar_arrive(BAR(B_ZRDY));
            TS(2);
            za[6] = za[7] = 0u;
            cvt(pk, 24);
            cvt(p2, 25);
#pragma unroll
            for (int i = 0; i < 6; i++) za[i] |= p2[7] & (ln >> 5);
            constexpr uint64_t d1 = make_desc(SB0 + OFF_SEF, 256, 128, 0), d2 = make_desc(SB0 + OFF_SEF + 1024, 512, 128, 0);
            float h[8], o[16];
#pragma unroll
            for (int i = 0; i < 16; i++) asm volatile("" : "=f"(o[i]), "=f"(h[i & 7]));
            wgmma_fence();
            wgmma_m64n16k16_rs<0>(h, za, d1);
            wgmma_m64n16k16_rs<1>(h, za + 4, d1 + 32);
            wgmma_commit();
            mma_h(I2{}, 1);
            mma_d(I3{}, 1);
            wgmma_wait<2>();
            const uint32_t ha0 = pack_bf16(gelu2(h[0]), gelu2(h[1])), ha1 = pack_bf16(gelu2(h[2]), gelu2(h[3])), ha2 = pack_bf16(gelu2(h[4]), gelu2(h[5])),
                           ha3 = pack_bf16(gelu2(h[6]), gelu2(h[7]));
            wgmma_fence();
            wgmma_m64n32k16_rs<2>(o, ha0, ha1, ha2, ha3, d2);
            wgmma_commit();
            wgmma_wait<2>();
            if (l0) mbar_arrive(BAR(B_EMPTY + 22));
            READY(24);
            mma_d(I0{}, 1);
            READY(25);
            store(pk, 24);
            store(p2, 25);
            wgmma_wait<1>();
            if (l0) mbar_arrive(BAR(B_EMPTY + 23));
            mma_d(I1{}, 1);
#pragma unroll
            for (int i = 0; i < 2; i++) {
                uint32_t a[4];
#pragma unroll
                for (int k = 0; k < 4; k++) a[k] = pack_bf16(fmaf(tanh_fast(o[8 * i + 2 * k]), 0.5f, 0.5f), fmaf(tanh_fast(o[8 * i + 2 * k + 1]), 0.5f, 0.5f));
                sts128(sb + OFF_AP + i * 2048 + warp * 512 + ln * 16, a[0], a[1], a[2], a[3]);
            }
            __syncwarp();
            if (l0) mbar_arrive(BAR(B_EWRDY));
            wgmma_wait<1>();
            if (l0) mbar_arrive(BAR(B_EMPTY + 24));
            TS(3);
        }
        {
            wgmma_wait<0>();
            if (l0) mbar_arrive(BAR(B_EMPTY + 25));
            uint32_t hw[32];
#pragma unroll
            for (int i = 0; i < 32; i++) asm volatile("cvt.rn.bf16x2.f32 %0, %1, %2;" : "=r"(hw[i]) : "f"(acc[2 * i + 1]), "f"(acc[2 * i]));
            asm volatile("setmaxnreg.dec.sync.aligned.u32 %0;" ::"n"(R_DEEP2));
            TS(4);
            float o[4] = {0.f, 0.f, 0.f, 0.f};
            int l2;
            asm volatile("mov.u32 %0, %%laneid;" : "=r"(l2));
#pragma unroll
            for (int it = 0; it < 8; it++) {
                uint32_t b0, b1;
                asm volatile("ld.shared.v2.u32 {%0,%1}, [%2];" : "=r"(b0), "=r"(b1) : "r"(sb + OFF_W2 + 8 * (l2 & 3) + it * 32));
                mma16816(o, gelu2p(hw[4 * it]), gelu2p(hw[4 * it + 1]), gelu2p(hw[4 * it + 2]), gelu2p(hw[4 * it + 3]), b0, b1);
            }
            send_partial(sb, rank * 3, warp, l2 >> 2, l2 & 3, 0.5f * o[0], 0.5f * o[2]);
        }
        TS(5);
    } else {
        const int wgc = (warp >> 2) - 1, w4 = warp & 3;
        const char* so = (const char*)table + 16 * (lane & 7);
        auto rp = [&](uint32_t i) { return row_ptr(so, i); };
        const uint32_t d0 = opq(sb + OFF_RT + b * 128 + (((lane ^ b) & 7) << 4)), d1 = opq((d0 ^ 64) + 6 * RT);
        {
            const int ia[4] = {i0a.x, i0a.y, i1a.x, i1a.y}, ib[4] = {i0b.x, i0b.y, i1b.x, i1b.y};
            static_for<0, NFIRST>([&](auto FC) {
                constexpr int f = decltype(FC)::value, o = (f >> 1) * RT;
                cp_async16(((f & 1) ? d1 : d0) + o, rp(ia[f]));
                cp_async16(((f & 1) ? d1 : d0) + o + 4096, rp(ib[f]));
                if (f & 1) cp_async_mbar_arrive_noinc(BAR(B_PAIR + (f >> 1)));
            });
            if (wgc == 0) TS(6);
        }
        asm volatile("setmaxnreg.inc.sync.aligned.u32 %0;" ::"n"(R_CR1));
        uint32_t M[8][12], y[4][2];
        {
            const uint32_t pa = opq(sb + OFF_RT + (t & 1) * 6 * RT + (16 * w4 + g) * 128 + (((4 * rank + 2 * wgc) ^ g ^ (4 * (t & 1))) << 4)), t1 = opq(t >> 1);
            const uint32_t ia = opq(sb + OFF_IDX + b * NF * 4);
#pragma unroll
            for (int i = 0; i < 96; i++) asm volatile("" : "=r"(M[i / 12][i % 12]));
            mbar_wait(BAR(B_IDX), 0);
            uint32_t x[13][4];
#pragma unroll
            for (int p = 2; p < 13; p++)
                asm volatile("ld.shared.v2.u32 {%0,%1}, [%4];\nld.shared.v2.u32 {%2,%3}, [%4 + 3328];" : "=r"(x[p][0]), "=r"(x[p][2]), "=r"(x[p][1]), "=r"(x[p][3]) : "r"(ia + p * 8));
            const uint32_t pb = opq(pa ^ 16);
            auto conv = [&](int G) {
#pragma unroll
                for (int i = 0; i < 16; i++) {
                    uint32_t &u = M[i >> 1][4 * G + 2 * (i & 1)], &v = M[i >> 1][4 * G + 2 * (i & 1) + 1];
                    asm volatile("{\n.reg .b32 t;\nprmt.b32 t, %0, %1, 0x5410;\nprmt.b32 %1, %0, %1, 0x7632;\nmov.b32 %0, t;\n}\n" : "+r"(u), "+r"(v));
                }
#pragma unroll
                for (int i = 0; i < 8; i++)
                    asm volatile("{\n.reg .pred p;\nsetp.eq.u32 p, %5, 2;\n@p st.shared.v4.u32 [%4], {%0,%1,%2,%3};\n}\n" ::"r"(M[i & 4][4 * G + (i & 3)]), "r"(M[(i & 4) + 1][4 * G + (i & 3)]),
                                 "r"(M[(i & 4) + 2][4 * G + (i & 3)]), "r"(M[(i & 4) + 3][4 * G + (i & 3)]), "r"(pa), "r"(t1));
            };
            static_for<0, 15>([&](auto QC) {
                constexpr int q = decltype(QC)::value - 3, p = (int)(0x0C0BA9876054302ull >> (4 * q + 12)) & 15;
                if (q > 2) mbar_wait(BAR(B_EMPTY + 2 * q - 6), 0);
                if (q > 0) mbar_wait(BAR(B_PAIR + q), 0);
                if (p == 3) mbar_wait(BAR(B_PAIR), 0);
                if (p) {
                    constexpr uint32_t o1 = (p < 12 ? p : 7) * RT;
                    cp_async16(d0 + p * RT, rp(x[p][0]));
                    cp_async16(d0 + p * RT + 4096, rp(x[p][1]));
                    cp_async16(d1 + o1, rp(x[p][2]));
                    cp_async16(d1 + o1 + 4096, rp(x[p][3]));
                    cp_async_mbar_arrive_noinc(BAR(B_PAIR + p));
                }
                if (q == 0) mbar_wait(BAR(B_PAIR), 0);
                if constexpr (q >= 0) {
                    constexpr int c = 4 * (q >> 2) + ((q >> 1) & 1);
#pragma unroll
                    for (int i = 0; i < 4; i++)
                        asm volatile("{\n.reg .pred p;\nsetp.eq.u32 p, %5, %6;\n@p ld.shared.v4.u32 {%0,%1,%2,%3}, [%4];\n}\n"
                                     : "+r"(M[2 * (i & 2)][c + 2 * (i & 1)]), "+r"(M[2 * (i & 2) + 1][c + 2 * (i & 1)]), "+r"(M[2 * (i & 2) + 2][c + 2 * (i & 1)]),
                                       "+r"(M[2 * (i & 2) + 3][c + 2 * (i & 1)])
                                     : "r"(((i & 2) ? pb : pa) + q * RT + (i & 1) * 1024), "r"(t1), "n"(q & 1));
                    __syncwarp();
                    if (elect_one()) mbar_arrive(BAR(B_W + 2 * q + 1));
                    if (q == 4 || q == 8) conv(q / 4 - 1);
                }
            });
            const uint32_t ta = sb + OFF_RT + 12 * RT + (16 * w4 + g) * 128 + (((4 * rank + 2 * wgc + (t >> 1)) ^ g) << 4) + 8 * (t & 1);
            mbar_wait(BAR(B_PAIR + 12), 0);
#pragma unroll
            for (int k = 0; k < 4; k++) asm volatile("ld.shared.v2.u32 {%0,%1}, [%2];" : "=r"(y[k][0]), "=r"(y[k][1]) : "r"(((k & 1) ? (ta ^ 64) + RT : ta) + (k >> 1) * 1024));
            __syncwarp();
            if (elect_one()) mbar_arrive(BAR(B_W + 25));
            conv(2);
        }
        uint32_t TL[4][2];
        uint32_t ap[8], a0, a1;
        mbar_wait(BAR(B_CFULL), 0);
        mbar_wait(BAR(B_EWRDY), 0);
        if (wgc == 0) TS(60);
        asm volatile("setmaxnreg.inc.sync.aligned.u32 %0;" ::"n"(R_CR2));
        if (wgc == 0) TS(61);
        {
            int l2;
            asm volatile("mov.u32 %0, %%laneid;" : "=r"(l2));
            const int r = l2 & 7, bh = (l2 >> 3) & 1, ig = l2 >> 4;
            const uint32_t x = sb + OFF_EW + wgc * 256 + (2 * w4 + bh) * 512 + (8 * ig + 4 * (r & 1) + (r >> 1)) * EWP;
            a0 = opq(x);
            a1 = opq(x + (!ig || r == 0 ? 16 : r == 1 ? 13 : 8) * EWP);
#pragma unroll
            for (int i = 0; i < 2; i++) {
                const uint4 v = lds128(sb + OFF_AP + i * 2048 + w4 * 512 + l2 * 16);
                ap[4 * i] = v.x, ap[4 * i + 1] = v.y, ap[4 * i + 2] = v.z, ap[4 * i + 3] = v.w;
            }
        }
        constexpr uint64_t dt = make_desc(SB0 + OFF_TW, 512, 128, 0), dqc = make_desc(SB0 + OFF_ID, 128, 128, 0);
        const uint64_t dq = uni64(dqc + (sb >> 28));
        const uint64_t desc = dt + wgc * (CHUNK >> 4);
        auto dsc = [&](int e, int pq) { return desc + ((CPOS >> (4 * (e >> 1))) & 7) * (2 * CHUNK >> 4) + ((e & 1) * 2 + pq) * (TILE >> 4); };
        float S[4], accP[16], accQ[16];
#pragma unroll
        for (int i = 0; i < 16; i++) asm volatile("" : "=f"(accP[i]), "=f"(accQ[i]));
        uint32_t A0[8], A1[8], Aq[8], w[8];
        u_lda(A0, a0, a1);
        u_lda(A1, a0 + 16, a1 + 16);
#pragma unroll
        for (int k = 0; k < 8; k++) asm volatile("prmt.b32 %0, %1, %2, %3;" : "=r"(TL[k >> 1][k & 1]) : "r"(y[2 * (k & 1)][k >> 2]), "r"(y[2 * (k & 1) + 1][k >> 2]), "r"(0x5410 + 0x2222 * ((k >> 1) & 1)));
#pragma unroll
        for (int i = 0; i < 4; i++) asm volatile("" : "=f"(S[i]));
#pragma unroll
        for (int k = 0; k < 8; k++) Aq[k] = hmul2_bf16(A0[k], ap[k]);
        wgmma_fence();
        u_mma(accP, A0, dsc(0, 0));
        wgmma_commit();
        u_mma(accQ, Aq, dsc(0, 1));
        wgmma_commit();
        if (wgc == 0) TS(62);
        auto pack8 = [&](uint32_t (&d)[8], const float (&a)[16]) {
#pragma unroll
            for (int k = 0; k < 8; k++) asm volatile("cvt.rn.bf16x2.f32 %0, %1, %2;" : "=r"(d[k]) : "f"(a[2 * k + 1]), "f"(a[2 * k]));
        };
        static_for<0, 8>([&](auto PC) {
            constexpr int p = decltype(PC)::value, e = 2 * p;
            auto mw = [&](int s, int k) { return k < 6 ? M[p][2 * k + s] : TL[(e + s) & 3][k - 6]; };
            uint32_t tp[8], tq[8];
            wgmma_wait<1>();
            pack8(tp, accP);
            wgmma_fence();
            u_mma(accP, A1, dsc(e + 1, 0));
            if (p) {
                wgmma_m64n8k16_rs(S, w, dq, p > 1);
                wgmma_m64n8k16_rs(S, w + 4, dq, 1);
            }
            wgmma_commit();
            if (p < 7) u_lda(A0, a0 + 16 * e + 32, a1 + 16 * e + 32);
            wgmma_wait<1>();
            pack8(tq, accQ);
#pragma unroll
            for (int k = 0; k < 8; k++) Aq[k] = hmul2_bf16(A1[k], ap[k]);
            wgmma_fence();
            u_mma(accQ, Aq, dsc(e + 1, 1));
            wgmma_commit();
#pragma unroll
            for (int k = 0; k < 8; k++) tq[k] = hfma2_bf16(tq[k], ap[k], tp[k]);
            if (p == 0 || p == 2 || p == 5) mbar_wait(BAR(B_CFULL + 1 + p / 2), 0);
            wgmma_wait<1>();
            pack8(tp, accP);
            if (p < 7) {
                wgmma_fence();
                u_mma(accP, A0, dsc(e + 2, 0));
                wgmma_commit();
                u_lda(A1, a0 + 16 * e + 48, a1 + 16 * e + 48);
            }
#pragma unroll
            for (int k = 0; k < 8; k++) w[k] = hmul2_bf16(tq[k], mw(0, k));
            wgmma_wait<(p < 7)>();
            if (p == 0 && elect_one()) mbar_arrive(BAR(B_CDONE));
            pack8(tq, accQ);
            if (p < 7) {
#pragma unroll
                for (int k = 0; k < 8; k++) Aq[k] = hmul2_bf16(A0[k], ap[k]);
                wgmma_fence();
                u_mma(accQ, Aq, dsc(e + 2, 1));
                wgmma_commit();
            }
#pragma unroll
            for (int k = 0; k < 8; k++) w[k] = hfma2_bf16(hfma2_bf16(tq[k], ap[k], tp[k]), mw(1, k), w[k]);
        });
        int tid2;
        asm volatile("mov.u32 %0, %%laneid;" : "=r"(tid2));
        wgmma_fence();
        wgmma_m64n8k16_rs(S, w, dq, 1);
        wgmma_m64n8k16_rs(S, w + 4, dq, 1);
        wgmma_commit();
        wgmma_wait<0>();
        send_partial(sb, rank * 3 + 1 + wgc, w4, tid2 >> 2, tid2 & 3, S[0], S[2]);
        if (wgc == 0) TS(14);
    }
#undef BAR
}

typedef CUresult (*PFN_encodeTiled)(CUtensorMap*, CUtensorMapDataType, cuuint32_t, void*, const cuuint64_t*, const cuuint64_t*,
                                    const cuuint32_t*, const cuuint32_t*, CUtensorMapInterleave, CUtensorMapSwizzle,
                                    CUtensorMapL2promotion, CUtensorMapFloatOOBfill);

}

extern "C" void kernel_launch(void* const* d_in, const int* in_sizes, int n_in, void* d_out, int out_size) {
    const int* idx = (const int*)d_in[0];
    const __nv_bfloat16* table = (const __nv_bfloat16*)d_in[1];
    const __nv_bfloat16* se_w1 = (const __nv_bfloat16*)d_in[2];
    const __nv_bfloat16* se_w2 = (const __nv_bfloat16*)d_in[3];
    const __nv_bfloat16* w_bi = (const __nv_bfloat16*)d_in[4];
    const __nv_bfloat16* w_cross = (const __nv_bfloat16*)d_in[5];
    const __nv_bfloat16* w_deep1 = (const __nv_bfloat16*)d_in[6];
    const __nv_bfloat16* w_deep2 = (const __nv_bfloat16*)d_in[7];
    __nv_bfloat16* out = (__nv_bfloat16*)d_out;

    static PFN_encodeTiled enc = nullptr;
    if (!enc) {
        void* fn = nullptr;
        cudaDriverEntryPointQueryResult qres;
        cudaGetDriverEntryPoint("cuTensorMapEncodeTiled", &fn, cudaEnableDefault, &qres);
        enc = (PFN_encodeTiled)fn;
        cudaFuncSetAttribute(fused_kernel, cudaFuncAttributeMaxDynamicSharedMemorySize, SMEM);
    }
    CUtensorMap tm;
    {
        cuuint64_t gdim[3] = {64, (cuuint64_t)(NF * ND), 4};
        cuuint64_t gstr[2] = {(cuuint64_t)NH * 2, 128};
        cuuint32_t box[3] = {64, 64, 2};
        cuuint32_t estr[3] = {1, 1, 1};
        enc(&tm, CU_TENSOR_MAP_DATA_TYPE_BFLOAT16, 3, (void*)w_deep1, gdim, gstr, box, estr, CU_TENSOR_MAP_INTERLEAVE_NONE,
            CU_TENSOR_MAP_SWIZZLE_128B, CU_TENSOR_MAP_L2_PROMOTION_L2_256B, CU_TENSOR_MAP_FLOAT_OOB_FILL_NONE);
    }
    fused_kernel<<<128, 512, SMEM>>>(idx, table, w_deep1, w_bi, w_deep2, w_cross, se_w1, se_w2, out, tm);
}
```

```cpp
#include <cuda_runtime.h>
#include <cuda_bf16.h>
#include <cuda.h>
#include <stdint.h>
#include <type_traits>
#include <utility>

#define R_DEEP 216
#define R_CR1 136
#define R_CR2 216
#define R_DEEP2 56
#define R_PROD 24

namespace {

constexpr int NF = 26, ND = 64, NH = 256, NFR = 13;

#define TS(slot)
#define TSL(slot)

__device__ __forceinline__ uint32_t smem_u32(const void* p) { return (uint32_t)__cvta_generic_to_shared(p); }
__device__ __forceinline__ void mbar_init(uint32_t bar, uint32_t cnt) {
    asm volatile("mbarrier.init.shared::cta.b64 [%0], %1;" ::"r"(bar), "r"(cnt));
}
__device__ __forceinline__ void mbar_expect_tx(uint32_t bar, uint32_t bytes) {
    asm volatile("mbarrier.arrive.expect_tx.shared::cta.b64 _, [%0], %1;" ::"r"(bar), "r"(bytes) : "memory");
}
__device__ __forceinline__ void mbar_arrive(uint32_t bar) {
    asm volatile("mbarrier.arrive.shared::cta.b64 _, [%0];" ::"r"(bar) : "memory");
}
__device__ __forceinline__ void mbar_wait(uint32_t bar, uint32_t parity) {
    asm volatile(
        "{\n"
        ".reg .pred p;\n"
        "WAIT_%=:\n"
        "mbarrier.try_wait.parity.shared::cta.b64 p, [%0], %1;\n"
        "@p bra.uni DONE_%=;\nbra.uni WAIT_%=;\nDONE_%=:\n"
        "}\n" ::"r"(bar),
        "r"(parity)
        : "memory");
}
__device__ __forceinline__ uint32_t opq(uint32_t x) { return __shfl_xor_sync(0xffffffffu, x, 0); }
__device__ __forceinline__ uint64_t uni64(uint64_t x) {
    uint32_t lo = (uint32_t)x, hi = (uint32_t)(x >> 32);
    asm volatile("shfl.sync.idx.b32 %0, %0, 0, 31, -1;\nshfl.sync.idx.b32 %1, %1, 0, 31, -1;" : "+r"(lo), "+r"(hi));
    return ((uint64_t)hi << 32) | lo;
}
__device__ __forceinline__ bool elect_one() {
    uint32_t r;
    asm volatile("{\n.reg .pred p;\nelect.sync _|p, 0xffffffff;\nselp.u32 %0, 1, 0, p;\n}\n" : "=r"(r));
    return r;
}
__device__ __forceinline__ const void* row_ptr(const void* base, uint32_t i) {
    const void* r;
    asm("mad.wide.u32 %0, %1, 128, %2;" : "=l"(r) : "r"(i), "l"(base));
    return r;
}
__device__ __forceinline__ void mbar_wait_bounded(uint32_t bar, uint32_t parity) {
    asm volatile(
        "{\n"
        ".reg .pred p;\n"
        ".reg .u32 c;\n"
        "mov.u32 c, 0;\n"
        "WAIT_%=:\n"
        "mbarrier.try_wait.parity.shared::cta.b64 p, [%0], %1;\n"
        "@p bra.uni DONE_%=;\n"
        "add.u32 c, c, 1;\n"
        "setp.lt.u32 p, c, 0x400000;\n"
        "@p bra.uni WAIT_%=;\n"
        "trap;\n"
        "DONE_%=:\n"
        "}\n" ::"r"(bar),
        "r"(parity)
        : "memory");
}
__device__ __forceinline__ void cp_async16(uint32_t dst, const void* src) {
    asm volatile("cp.async.cg.shared.global [%0], [%1], 16;" ::"r"(dst), "l"(src) : "memory");
}
__device__ __forceinline__ void cp_async_mbar_arrive_noinc(uint32_t bar) {
    asm volatile("cp.async.mbarrier.arrive.noinc.shared::cta.b64 [%0];" ::"r"(bar) : "memory");
}
__device__ __forceinline__ void tma_load_3d(uint32_t dst, const void* tmap, int c0, int c1, int c2, uint32_t bar) {
    asm volatile(
        "cp.async.bulk.tensor.3d.shared::cluster.global.mbarrier::complete_tx::bytes [%0], [%1, {%3, %4, %5}], [%2];" ::"r"(dst),
        "l"(tmap), "r"(bar), "r"(c0), "r"(c1), "r"(c2)
        : "memory");
}
__device__ __forceinline__ void bulk_load(uint32_t dst, const void* src, uint32_t bytes, uint32_t bar) {
    asm volatile("cp.async.bulk.shared::cluster.global.mbarrier::complete_tx::bytes [%0], [%1], %2, [%3];" ::"r"(dst), "l"(src), "r"(bytes),
                 "r"(bar)
                 : "memory");
}
__device__ __forceinline__ void fence_proxy_async() { asm volatile("fence.proxy.async.shared::cta;" ::: "memory"); }
__device__ __forceinline__ void wgmma_fence() { asm volatile("wgmma.fence.sync.aligned;" ::: "memory"); }
__device__ __forceinline__ void wgmma_commit() { asm volatile("wgmma.commit_group.sync.aligned;" ::: "memory"); }
template <int N> __device__ __forceinline__ void wgmma_wait() { asm volatile("wgmma.wait_group.sync.aligned %0;" ::"n"(N) : "memory"); }

__device__ __forceinline__ void ldsm_x4(uint32_t addr, uint32_t& r0, uint32_t& r1, uint32_t& r2, uint32_t& r3) {
    asm volatile("ldmatrix.sync.aligned.m8n8.x4.shared.b16 {%0,%1,%2,%3}, [%4];" : "=r"(r0), "=r"(r1), "=r"(r2), "=r"(r3) : "r"(addr));
}
__device__ __forceinline__ void ldsm_x4_t(uint32_t addr, uint32_t& r0, uint32_t& r1, uint32_t& r2, uint32_t& r3) {
    asm volatile("ldmatrix.sync.aligned.m8n8.x4.trans.shared.b16 {%0,%1,%2,%3}, [%4];" : "=r"(r0), "=r"(r1), "=r"(r2), "=r"(r3) : "r"(addr));
}
__device__ __forceinline__ void stsm_x4_t(uint32_t addr, uint32_t r0, uint32_t r1, uint32_t r2, uint32_t r3) {
    asm volatile("stmatrix.sync.aligned.m8n8.x4.trans.shared.b16 [%0], {%1,%2,%3,%4};" ::"r"(addr), "r"(r0), "r"(r1), "r"(r2), "r"(r3) : "memory");
}
__device__ __forceinline__ uint4 lds128(uint32_t addr) {
    uint4 v;
    asm volatile("ld.shared.v4.u32 {%0,%1,%2,%3}, [%4];" : "=r"(v.x), "=r"(v.y), "=r"(v.z), "=r"(v.w) : "r"(addr));
    return v;
}
__device__ __forceinline__ uint32_t lds32(uint32_t addr) {
    uint32_t v;
    asm volatile("ld.shared.u32 %0, [%1];" : "=r"(v) : "r"(addr));
    return v;
}
__device__ __forceinline__ void sts128(uint32_t addr, uint32_t a, uint32_t b, uint32_t c, uint32_t d) {
    asm volatile("st.shared.v4.u32 [%0], {%1,%2,%3,%4};" ::"r"(addr), "r"(a), "r"(b), "r"(c), "r"(d) : "memory");
}
__device__ __forceinline__ void mma16816(float (&c)[4], uint32_t a0, uint32_t a1, uint32_t a2, uint32_t a3, uint32_t b0, uint32_t b1) {
    asm("mma.sync.aligned.m16n8k16.row.col.f32.bf16.bf16.f32 {%0,%1,%2,%3}, {%4,%5,%6,%7}, {%8,%9}, {%0,%1,%2,%3};"
        : "+f"(c[0]), "+f"(c[1]), "+f"(c[2]), "+f"(c[3])
        : "r"(a0), "r"(a1), "r"(a2), "r"(a3), "r"(b0), "r"(b1));
}
__device__ __forceinline__ uint32_t pack_bf16(float lo, float hi) {
    uint32_t r;
    asm("cvt.rn.bf16x2.f32 %0, %1, %2;" : "=r"(r) : "f"(hi), "f"(lo));
    return r;
}
__device__ __forceinline__ uint32_t hmul2_bf16(uint32_t a, uint32_t b) {
    uint32_t r;
    asm("mul.rn.bf16x2 %0, %1, %2;" : "=r"(r) : "r"(a), "r"(b));
    return r;
}
__device__ __forceinline__ float tanh_fast(float x) {
    float r;
    asm("tanh.approx.f32 %0, %1;" : "=f"(r) : "f"(x));
    return r;
}
#define WG_ACC8(c, b) c(acc[b]), c(acc[b + 1]), c(acc[b + 2]), c(acc[b + 3]), c(acc[b + 4]), c(acc[b + 5]), c(acc[b + 6]), c(acc[b + 7])
#define WG_N128(c, sc)                                                                                                              \
    asm volatile(                                                                                                                   \
        "{\n"                                                                                                                       \
        ".reg .pred p;\n"                                                              \
        "setp.ne.b32 p, " sc ", 0;\n"                                                                                               \
        "wgmma.mma_async.sync.aligned.m64n128k16.f32.bf16.bf16 "                                                                    \
        "{%0,%1,%2,%3,%4,%5,%6,%7,%8,%9,%10,%11,%12,%13,%14,%15,"                                                                   \
        "%16,%17,%18,%19,%20,%21,%22,%23,%24,%25,%26,%27,%28,%29,%30,%31,"                                                          \
        "%32,%33,%34,%35,%36,%37,%38,%39,%40,%41,%42,%43,%44,%45,%46,%47,"                                                          \
        "%48,%49,%50,%51,%52,%53,%54,%55,%56,%57,%58,%59,%60,%61,%62,%63},"                                                         \
        " {%64,%65,%66,%67}, %68, p, 1, 1, 1;\n"                                                                                    \
        "}\n"                                                                                                                       \
        : WG_ACC8(c, 0), WG_ACC8(c, 8), WG_ACC8(c, 16), WG_ACC8(c, 24), WG_ACC8(c, 32), WG_ACC8(c, 40), WG_ACC8(c, 48), WG_ACC8(c, 56) \
        : "r"(a[0]), "r"(a[1]), "r"(a[2]), "r"(a[3]), "l"(db), "r"(scv))
__device__ __forceinline__ void wgmma_m64n128k16_rs_tb(float (&acc)[64], const uint32_t (&a)[4], uint64_t db, int scv) {
    WG_N128("+f", "%69");
}
#define WG_N40(c, sc)                                                                         \
    asm volatile(                                                                             \
        "{\n"                                                                                 \
        ".reg .pred p;\n"                        \
        "setp.ne.b32 p, " sc ", 0;\n"                                                         \
        "wgmma.mma_async.sync.aligned.m64n40k16.f32.bf16.bf16 "                               \
        "{%0,%1,%2,%3,%4,%5,%6,%7,%8,%9,%10,%11,%12,%13,%14,%15,%16,%17,%18,%19},"            \
        " {%20,%21,%22,%23}, %24, p, 1, 1, 1;\n"                                              \
        "}\n"                                                                                 \
        : WG_ACC8(c, 0), WG_ACC8(c, 8), c(acc[16]), c(acc[17]), c(acc[18]), c(acc[19])        \
        : "r"(a[0]), "r"(a[1]), "r"(a[2]), "r"(a[3]), "l"(db))
template <int SC>
__device__ __forceinline__ void wgmma_m64n40k16_rs_tb(float (&acc)[20], const uint32_t (&a)[4], uint64_t db) {
    if constexpr (SC == 1) WG_N40("+f", "1");
    else if constexpr (SC == 2) WG_N40("+f", "0");
    else WG_N40("=f", "0");
}
#define WG_N32(c, sc)                                                   \
    asm volatile(                                                       \
        "{\n"                                                           \
        ".reg .pred p;\n"           \
        "setp.ne.b32 p, " sc ", 0;\n"                                   \
        "wgmma.mma_async.sync.aligned.m64n32k16.f32.bf16.bf16 "         \
        "{%0,%1,%2,%3,%4,%5,%6,%7,%8,%9,%10,%11,%12,%13,%14,%15},"      \
        " {%16,%17,%18,%19}, %20, p, 1, 1, 0;\n"                        \
        "}\n"                                                           \
        : WG_ACC8(c, 0), WG_ACC8(c, 8)                                  \
        : "r"(a0), "r"(a1), "r"(a2), "r"(a3), "l"(db))
template <int SC>
__device__ __forceinline__ void wgmma_m64n32k16_rs(float (&acc)[16], uint32_t a0, uint32_t a1, uint32_t a2, uint32_t a3, uint64_t db) {
    if constexpr (SC == 1) WG_N32("+f", "1");
    else if constexpr (SC == 2) WG_N32("+f", "0");
    else WG_N32("=f", "0");
}

__host__ __device__ constexpr uint64_t make_desc(uint32_t addr, uint32_t lbo_bytes, uint32_t sbo_bytes, uint32_t swz) {
    uint64_t d = 0;
    d |= (uint64_t)((addr & 0x3FFFF) >> 4);
    d |= (uint64_t)((lbo_bytes >> 4) & 0x3FFF) << 16;
    d |= (uint64_t)((sbo_bytes >> 4) & 0x3FFF) << 32;
    d |= (uint64_t)swz << 62;
    return d;
}
__device__ __forceinline__ uint32_t ldg_u16(const __nv_bfloat16* p) { return (uint32_t)__ldg(reinterpret_cast<const unsigned short*>(p)); }
template <int N, class F, int... I>
__device__ __forceinline__ void static_for_impl(F&& f, std::integer_sequence<int, I...>) {
    (f(std::integral_constant<int, N + I>{}), ...);
}
template <int B, int E, class F>
__device__ __forceinline__ void static_for(F&& f) {
    static_for_impl<B>(f, std::make_integer_sequence<int, E - B>{});
}

__device__ __forceinline__ uint32_t hfma2_bf16(uint32_t a, uint32_t b, uint32_t c) {
    uint32_t r;
    asm("fma.rn.bf16x2 %0, %1, %2, %3;" : "=r"(r) : "r"(a), "r"(b), "r"(c));
    return r;
}
__device__ __forceinline__ float gelu2(float x) {
    const float k0 = 0.7978845608028654f, k01 = 0.7978845608028654f * 0.044715f;
    return fmaf(x, tanh_fast(x * fmaf(x * x, k01, k0)), x);
}
__device__ __forceinline__ uint32_t gelu2p(uint32_t x) {
    uint32_t t;
    const uint32_t u = hmul2_bf16(x, hfma2_bf16(hmul2_bf16(x, x), 0x3D123D12u, 0x3F4C3F4Cu));
    asm("tanh.approx.bf16x2 %0, %1;" : "=r"(t) : "r"(u));
    return hfma2_bf16(x, t, x);
}
__device__ __forceinline__ void wgmma_m64n8k16_rs(float (&acc)[4], const uint32_t* a, uint64_t db, int sc) {
    asm volatile("{\n.reg .pred p;\nsetp.ne.b32 p, %9, 0;\nwgmma.mma_async.sync.aligned.m64n8k16.f32.bf16.bf16 {%0,%1,%2,%3}, {%4,%5,%6,%7}, %8, p, 1, 1, 0;\n}\n"
                 : "+f"(acc[0]), "+f"(acc[1]), "+f"(acc[2]), "+f"(acc[3])
                 : "r"(a[0]), "r"(a[1]), "r"(a[2]), "r"(a[3]), "l"(db), "r"(sc));
}

template <int SC>
__device__ __forceinline__ void wgmma_m64n16k16_rs(float (&acc)[8], const uint32_t* a, uint64_t db) {
    asm volatile("{\n.reg .pred p;\nsetp.ne.b32 p, %13, 0;\nwgmma.mma_async.sync.aligned.m64n16k16.f32.bf16.bf16 {%0,%1,%2,%3,%4,%5,%6,%7}, {%8,%9,%10,%11}, %12, p, 1, 1, 0;\n}\n"
                 : WG_ACC8("+f", 0)
                 : "r"(a[0]), "r"(a[1]), "r"(a[2]), "r"(a[3]), "l"(db), "n"(SC));
}

constexpr int SB0 = 1024;
constexpr int SLOT = 4096;
constexpr int EWP = SLOT + 16;
constexpr int OFF_EW = 608;
constexpr int OFF_RT = 1024;
constexpr int RT = 8192;
constexpr int OFF_TW = OFF_RT + 13 * RT;
constexpr int HS_BYTES = 16384;
constexpr int OFF_RING = OFF_RT + 19 * RT;
constexpr int OFF_WBI = OFF_RT + 18 * RT;
constexpr int OFF_IDX = OFF_RT + 17 * RT;
constexpr int OFF_SEF = OFF_RING + 4 * HS_BYTES;
constexpr int OFF_AP = OFF_SEF + 2048;
constexpr int OFF_W2 = 0;
constexpr int OFF_DP = OFF_AP + 4096;
constexpr int OFF_ID = OFF_DP + 6 * 32 * 4;
constexpr int OFF_BAR = OFF_ID + 256;
constexpr int TILE = 2048;
constexpr int CHUNK = 4 * TILE;
constexpr int NCHUNK = 16;
constexpr int CPOS = 0x16504321;
static_assert(OFF_TW + 14 * CHUNK == OFF_SEF && OFF_EW + 25 * EWP + SLOT <= OFF_TW, "layout");
static_assert(OFF_RING % 1024 == 0 && OFF_WBI % 1024 == 0 && OFF_ID % 128 == 0, "align");
constexpr int B_CFULL = 0,
              B_F = 4,
              B_W = 16,
              B_EMPTY = 48, B_ZRDY = B_EMPTY + NF, B_CDONE = B_ZRDY + 1,
              B_EWRDY = B_CDONE + 2, B_PAIR = 80,
              B_IDX = B_PAIR + 13, B_FIN = B_PAIR + 14;
constexpr int OFF_TS = OFF_BAR + 768;
constexpr int SMEM = OFF_TS + 512;
static_assert(SMEM <= 232448, "smem");
constexpr int NFIRST = 4;
constexpr int JIT = 4;
constexpr int NUNIT = 128;

__device__ __align__(1024) uint8_t g_wt[2 * NCHUNK * CHUNK];
__device__ unsigned int g_cnt;

__device__ __forceinline__ void u_lda(uint32_t (&A)[8], uint32_t a0, uint32_t a1) {
    ldsm_x4_t(a0, A[0], A[1], A[2], A[3]);
    ldsm_x4_t(a1, A[4], A[5], A[6], A[7]);
}
__device__ __forceinline__ void u_mma(float (&acc)[16], const uint32_t (&A)[8], uint64_t desc) {
    wgmma_m64n32k16_rs<2>(acc, A[0], A[1], A[2], A[3], desc);
    wgmma_m64n32k16_rs<1>(acc, A[4], A[5], A[6], A[7], desc + 64);
}
__device__ __forceinline__ void send_partial(uint32_t sb, int src, int w4, int g, int t, float v0, float v1) {
    asm volatile("barrier.cluster.wait.acquire.aligned;" ::: "memory");
    if (t < 2) {
        uint32_t rb;
        asm volatile("mapa.shared::cluster.u32 %0, %1, %2;" : "=r"(rb) : "r"(sb), "r"(w4 >> 1));
        asm volatile("st.async.weak.shared::cluster.mbarrier::complete_tx::bytes.f32 [%0], %1, [%2];" ::"r"(rb + OFF_DP + (src * 32 + (w4 & 1) * 16 + 8 * t + g) * 4),
                     "f"(t ? v1 : v0), "r"(rb + OFF_BAR + B_FIN * 8)
                     : "memory");
    }
}

__global__ void __cluster_dims__(2, 1, 1) __launch_bounds__(512, 1)
fused_kernel(const int* __restrict__ idx, const __nv_bfloat16* __restrict__ table, const __nv_bfloat16* __restrict__ w1, const __nv_bfloat16* __restrict__ w_bi,
             const __nv_bfloat16* __restrict__ w2, const __nv_bfloat16* __restrict__ w_cross, const __nv_bfloat16* __restrict__ se_w1,
             const __nv_bfloat16* __restrict__ se_w2, __nv_bfloat16* __restrict__ out, const __grid_constant__ CUtensorMap tmW1) {
    extern __shared__ __align__(1024) uint8_t smem_raw[];
    const int tid = threadIdx.x, b = (tid >> 3) & 31;
    const int pb0 = (blockIdx.x >> 1) * 64;
    int2 i0a, i0b, i1a, i1b;
    asm volatile("ld.global.nc.v2.u32 {%0,%1}, [%8];\nld.global.nc.v2.u32 {%2,%3}, [%8 + 3328];\nld.global.nc.v2.u32 {%4,%5}, [%8 + 8];\nld.global.nc.v2.u32 {%6,%7}, [%8 + 3336];"
                 : "=r"(i0a.x), "=r"(i0a.y), "=r"(i0b.x), "=r"(i0b.y), "=r"(i1a.x), "=r"(i1a.y), "=r"(i1b.x), "=r"(i1b.y)
                 : "l"(idx + (pb0 + b) * NF));
    const uint32_t sb = __shfl_sync(0xffffffffu, smem_u32(smem_raw), 0);
    const uint32_t bars = sb + OFF_BAR;
#define BAR(i) (bars + (i) * 8)
    const int warp = __shfl_sync(0xffffffffu, tid >> 5, 0), lane = tid & 31, g = lane >> 2, t = lane & 3;
    const int rank = blockIdx.x & 1;
    if (tid == 0) TS(0);
    if (elect_one()) {
        mbar_init(BAR(B_PAIR + warp), warp < 13 ? 256 + (warp == 10) : 1);
        if (warp >= 13) {
            asm volatile("fence.mbarrier_init.release.cluster;" ::: "memory");
            mbar_expect_tx(BAR(B_PAIR + warp), warp == 13 ? 64 * NF * 4 : 6 * 32 * 4);
            if (warp == 13) bulk_load(sb + OFF_IDX, idx + pb0 * NF, 64 * NF * 4, BAR(B_IDX));
        }
        if (warp == 6) asm volatile("cp.async.bulk.prefetch.L2.global [%0], %1;" ::"l"((const char*)w1 + 4 * 32768 + blockIdx.x * 5632), "n"(5632) : "memory");
        mbar_init(BAR(16 + warp), ((0xAAAC >> warp) & 1) ? 9 : 1);
        mbar_init(BAR(32 + warp), (warp & 1) ? 9 : 1);
        mbar_init(BAR(48 + warp), 4);
        mbar_init(BAR(64 + warp), warp == B_CDONE - 64 ? 8 : 4);
        if (warp < 6) mbar_init(BAR(warp), warp < 4 ? (0x2321 >> (4 * warp)) & 3 : 256);
        asm volatile("fence.mbarrier_init.release.cluster;" ::: "memory");
    }
    __syncthreads();
    asm volatile("barrier.cluster.arrive.relaxed.aligned;" ::: "memory");
    if (tid == 0) TS(1);

    if (warp >= 12) {
        asm volatile("setmaxnreg.dec.sync.aligned.u32 %0;" ::"n"(R_PROD));
        if ((sb & 0xFFFFFFu) != SB0) __trap();
        if (warp == 12) {
#pragma unroll 1
            for (int f = 0; f < NF; f++) {
                if (f >= 4) mbar_wait_bounded(BAR(B_EMPTY + f - 4), 0);
                TSL(80 + f);
                if (elect_one()) {
                    mbar_expect_tx(BAR(B_W + f), HS_BYTES);
                    tma_load_3d(sb + OFF_RING + ((f + 2) & 3) * HS_BYTES, &tmW1, 0, f * 64, rank * 2, BAR(B_W + f));
                }
            }
            asm volatile("barrier.cluster.wait.acquire.aligned;" ::: "memory");
            mbar_wait_bounded(BAR(B_FIN), 0);
            float v = 0.f;
#pragma unroll
            for (int i = 0; i < 6; i++) v += __uint_as_float(lds32(sb + OFF_DP + (i * 32 + lane) * 4));
            out[pb0 + 32 * rank + lane] = __float2bfloat16_rn(v);
            TSL(15);
        } else {
            if (warp == 14) {
#pragma unroll 1
                for (int k = JIT; k < NF; k++) {
                    mbar_wait(BAR(B_PAIR + min((k + 3) >> 1, 12)), 0);
                    mbar_wait(BAR(B_W + k), 0);
                    asm volatile("bar.arrive %0, 160;" ::"r"(4 + (k & 3)) : "memory");
                }
            } else if (warp == 13) {
                const uint32_t sr = sb + OFF_AP;
                {
                    uint32_t v[12];
#pragma unroll
                    for (int i = 0; i < 12; i++) v[i] = lane + 32 * (i >> 1) < NF * NFR / 2 ? __ldg(reinterpret_cast<const uint32_t*>((i & 1) ? se_w2 : se_w1) + lane + 32 * (i >> 1)) : 0u;
#pragma unroll
                    for (int i = 0; i < 12; i++) asm volatile("st.shared.u32 [%0], %1;" ::"r"(sr + lane * 4 + (i >> 1) * 128 + (i & 1) * 1024), "r"(v[i]) : "memory");
                    __syncwarp();
                }
#pragma unroll 1
                for (int q = 0; q < 8; q++) {
                    const int c1 = 8 * (q & 1) + g, o1 = c1 < NFR ? min((8 * (q >> 1) + 2 * t) * NFR + c1, NF * NFR) : NF * NFR;
                    const int c2 = 8 * (q & 3) + ((q & 3) < 3 ? 4 * (g & 1) + (g >> 1) : (g & 1)), o2 = min((8 * (q >> 2) + 2 * t) * NF + c2, NF * NFR);
                    uint32_t y1, y2;
                    asm volatile("{\n.reg .b16 a, b, c, d;\nld.shared.b16 a, [%2];\nld.shared.b16 b, [%2 + 26];\nld.shared.b16 c, [%3 + 1024];\nld.shared.b16 d, [%3 + 1076];\n"
                                 "mov.b32 %0, {a, b};\nmov.b32 %1, {c, d};\n}\n" : "=r"(y1), "=r"(y2) : "r"(sr + 2 * o1), "r"(sr + 2 * o2));
                    asm volatile("st.shared.u32 [%0], %1;\nst.shared.u32 [%0 + 1024], %2;" ::"r"(sb + OFF_SEF + q * 128 + lane * 4), "r"(y1),
                                 "r"(hmul2_bf16(y2, 0x3E803E80u))
                                 : "memory");
                }
                fence_proxy_async();
                __syncwarp();
                TSL(12);
                if (elect_one()) mbar_arrive(BAR(B_PAIR + 10));
            } else {
                {
                    const int pq = blockIdx.x >> 6, js = (blockIdx.x >> 1) & 31;
                    const int j = js < 24 ? (js & 24) + 4 * (js & 1) + ((js >> 1) & 3) : 24 + (js & 1);
                    const bool on = js < 24 || ((js >> 1) & 3) == ((lane >> 2) & 3);
                    const __nv_bfloat16* s = w_cross + ((size_t)(pq * NF) * NF + j) * ND + 32 * rank + lane;
                    uint8_t* d = g_wt + (size_t)rank * NCHUNK * CHUNK + (((lane & 15) >> 1) * 2 + (lane >> 4)) * CHUNK + ((lane & 1) * 2 + pq) * TILE + js * 16;
#pragma unroll 1
                    for (int kh = 0; kh < 2; kh++) {
                        uint32_t x[8];
#pragma unroll
                        for (int k = 0; k < 8; k++)
                            x[k] = (on && (kh == 0 || k < 5)) ? ldg_u16(s + (k + (k & 4)) * NF * ND) | (ldg_u16(s + (k == 4 && kh ? 9 : k + (k & 4) + 4) * NF * ND) << 16) : 0u;
                        *reinterpret_cast<uint4*>(d) = make_uint4(x[0], x[1], x[2], x[3]);
                        *reinterpret_cast<uint4*>(d + 512) = make_uint4(x[4], x[5], x[6], x[7]);
                        s += 16 * NF * ND;
                        d += 1024;
                    }
                    __syncwarp();
                }
                TSL(8);
                if (elect_one()) asm volatile("red.release.gpu.global.inc.u32 [%0], %1;" ::"l"(&g_cnt), "n"(NUNIT + 127) : "memory");
                TSL(9);
                mbar_wait(BAR(B_EMPTY + 6), 0);
                TSL(10);
                unsigned int v;
                do {
                    asm volatile("ld.acquire.gpu.global.u32 %0, [%1];" : "=r"(v) : "l"(&g_cnt) : "memory");
                } while (v < NUNIT);
                asm volatile("fence.proxy.async.global;" ::: "memory");
                __syncwarp();
                if (elect_one()) asm volatile("red.relaxed.gpu.global.inc.u32 [%0], %1;" ::"l"(&g_cnt), "n"(NUNIT + 127) : "memory");
                TSL(11);
                const uint8_t* wsrc = g_wt + (size_t)rank * NCHUNK * CHUNK;
#pragma unroll 1
                for (int k = 0; k < 8; k++) {
                    mbar_wait(BAR(B_EMPTY + 20 + ((0x75493260 >> (4 * k)) & 15)), 0);
                    TSL(30 + k);
                    if (elect_one()) {
                        const uint32_t cf = BAR(B_CFULL + ((0x33222110 >> (4 * k)) & 3));
                        mbar_expect_tx(cf, 2 * CHUNK);
                        bulk_load(sb + OFF_TW + ((CPOS >> (4 * k)) & 7) * 2 * CHUNK, wsrc + k * 2 * CHUNK, 2 * CHUNK, cf);
                    }
                }
            }
            __syncwarp();
            asm volatile("barrier.cluster.wait.acquire.aligned;" ::: "memory");
        }
    } else if (warp < 4) {
        {
            const uint4* wb = reinterpret_cast<const uint4*>(w_bi + (tid >> 2) * 64 + 32 * rank + 8 * t);
            const uint4 wb0 = __ldg(wb), wb1 = __ldg(wb + 256);
            const uint32_t w2v = __ldg(reinterpret_cast<const uint32_t*>(w2) + rank * 64 + (tid & 63));
            sts128(sb + OFF_WBI + (tid & 63) * 128 + ((4 ^ (tid & 7)) << 4), 0x3C803C80u, 0x3C803C80u, 0x3C803C80u, 0x3C803C80u);
            asm volatile("st.shared.u32 [%0], %1;" ::"r"(sb + OFF_ID + (tid & 63) * 4), "r"(0x3F803F80u) : "memory");
            asm volatile("st.shared.u32 [%0], %1;" ::"r"(sb + OFF_W2 + (tid & 56) * 4 + (tid & 3) * 8 + (tid & 4)), "r"(w2v) : "memory");
            const uint32_t wd = sb + OFF_WBI + (tid >> 2) * 128 + ((t ^ (g & 7)) << 4);
            sts128(wd, wb0.x, wb0.y, wb0.z, wb0.w);
            sts128(wd + 4096, wb1.x, wb1.y, wb1.z, wb1.w);
            fence_proxy_async();
        }
        asm volatile("setmaxnreg.inc.sync.aligned.u32 %0;" ::"n"(R_DEEP));
        asm volatile("bar.sync 1, 128;" ::: "memory");
        TS(7);
        float acc[64];
        float e2[2][20];
#pragma unroll
        for (int i = 0; i < 64; i++) asm volatile("" : "=f"(acc[i]));
#pragma unroll
        for (int i = 0; i < 20; i++) asm volatile("" : "=f"(e2[0][i]), "=f"(e2[1][i]));
        uint32_t A[4][4][4];
        constexpr uint64_t dr = make_desc(SB0 + OFF_RING, 8192, 1024, 1), dwc = make_desc(SB0 + OFF_WBI, 4096, 1024, 1);
        const uint64_t dw = uni64(dwc + (sb >> 28));
        const uint32_t sa = opq((lane >> 4) * 128 + (2 * warp + ((lane >> 3) & 1)) * 512 + (lane & 7) * 16);
        const uint32_t ln = opq(lane);
        const bool l0 = ln == 0;
        uint32_t la[4];
#pragma unroll
        for (int i = 0; i < 4; i++) la[i] = opq((sb + OFF_RT + (16 * warp + (lane & 15)) * 128 + (((lane >> 4) ^ (lane & 7)) << 4)) ^ (i << 5));
        uint32_t za[8];
#pragma unroll
        for (int i = 0; i < 6; i++) asm volatile("" : "=r"(za[i]));
        auto cvt = [&](uint32_t (&pk)[8], int f) {
            const float(&e)[20] = e2[f & 1];
#pragma unroll
            for (int i = 0; i < 8; i++) asm volatile("cvt.rn.bf16x2.f32 %0, %1, %2;" : "=r"(pk[i]) : "f"(e[2 * i + 1]), "f"(e[2 * i]));
            uint32_t &z0 = za[2 * (f >> 3)], &z1 = za[2 * (f >> 3) + 1];
            asm volatile("{\n.reg .pred p;\nsetp.eq.u32 p, %6, %7;\n@p cvt.rn.bf16x2.f32 %0, %2, %4;\n@p cvt.rn.bf16x2.f32 %1, %3, %5;\n}\n"
                         : "+r"(z0), "+r"(z1)
                         : "f"(e[16]), "f"(e[18]), "f"((f & 1) ? __uint_as_float(z0) : 0.f), "f"((f & 1) ? __uint_as_float(z1) : 0.f), "r"(ln & 3), "r"((f >> 1) & 3));
        };
        auto store = [&](const uint32_t (&pk)[8], int f) {
            stsm_x4_t(sa + sb + OFF_EW + f * EWP, pk[0], pk[1], pk[2], pk[3]);
            stsm_x4_t(sa + sb + OFF_EW + f * EWP + 256, pk[4], pk[5], pk[6], pk[7]);
        };
        auto load1 = [&](auto VC, int i, uint32_t o) {
            constexpr int v = decltype(VC)::value;
            ldsm_x4(la[i ^ (2 * (v & 1))] + o, A[v][i][0], A[v][i][1], A[v][i][2], A[v][i][3]);
        };
        auto mma_e = [&](auto VC) {
            constexpr int v = decltype(VC)::value;
            uint32_t(&ai)[4][4] = A[v];
            wgmma_m64n40k16_rs_tb<2>(e2[v & 1], ai[0], dw);
            wgmma_m64n40k16_rs_tb<1>(e2[v & 1], ai[1], dw + 128);
            wgmma_m64n40k16_rs_tb<1>(e2[v & 1], ai[2], dw + 256);
            wgmma_m64n40k16_rs_tb<1>(e2[v & 1], ai[3], dw + 384);
        };
        auto mma_d1 = [&](auto VC, int i, int sc) {
            constexpr int v = decltype(VC)::value, st = (v + 2) & 3;
            wgmma_m64n128k16_rs_tb(acc, A[v][i], dr + st * (HS_BYTES >> 4) + 128 * i, sc);
        };
        auto mma_d = [&](auto VC, int sc) {
            wgmma_fence();
#pragma unroll
            for (int i = 0; i < 4; i++) mma_d1(VC, i, i ? 1 : sc);
            wgmma_commit();
        };
        auto mma_e1 = [&](auto VC) {
            wgmma_fence();
            mma_e(VC);
            wgmma_commit();
        };
        auto load = [&](auto VC, uint32_t o) {
#pragma unroll
            for (int i = 0; i < 4; i++) load1(VC, i, o);
        };
#define READY(k) asm volatile("bar.sync %0, 160;" ::"n"(4 + ((k) & 3)) : "memory")
        using I0 = std::integral_constant<int, 0>;
        using I1 = std::integral_constant<int, 1>;
        using I2 = std::integral_constant<int, 2>;
        using I3 = std::integral_constant<int, 3>;
        uint32_t pk[8];
        mbar_wait(BAR(B_F), 0);
        TS(19);
        load(I0{}, 0);
        static_for<0, JIT>([&](auto KC) {
            constexpr int k = decltype(KC)::value;
            std::integral_constant<int, k & 3> UC;
            if (k > 1) cvt(pk, k - 2);
            mma_e1(UC);
            mbar_wait(BAR(B_W + k), 0);
            mma_d(UC, k);
            wgmma_wait<2>();
            if (k > 0 && l0) mbar_arrive(BAR(B_EMPTY + k - 1));
            if (k > 1) store(pk, k - 2);
            mbar_wait(BAR(((k & 1) && k < JIT - 1 ? B_F : B_PAIR) + (k + 1) / 2), 0);
            load(std::integral_constant<int, (k + 1) & 3>{}, ((k + 1 + 11 * (~k & 1)) / 2) * RT);
        });
        load(std::integral_constant<int, (JIT + 1) & 3>{}, ((JIT + 12) / 2) * RT);
        mbar_wait(BAR(B_PAIR + JIT / 2 + 1), 0);
        TS(20);
        static_for<JIT, 22>([&](auto KC) {
            constexpr int k = decltype(KC)::value;
            std::integral_constant<int, k & 3> UC;
            cvt(pk, k - 2);
            store(pk, k - 2);
            load(std::integral_constant<int, (k & 3) ^ 2>{}, ((k + 2 + 11 * (k & 1)) / 2) * RT);
            mma_e1(UC);
            READY(k);
            mma_d(UC, 1);
            wgmma_wait<2>();
            if (l0) mbar_arrive(BAR(B_EMPTY + k - 1));
        });
        {
            uint32_t p2[8];
            cvt(pk, 20);
            store(pk, 20);
            load(I0{}, 12 * RT);
            mma_e1(I2{});
            wgmma_wait<2>();
            cvt(pk, 21);
            mma_e1(I3{});
            store(pk, 21);
            READY(22);
            READY(23);
            wgmma_wait<2>();
            if (l0) mbar_arrive(BAR(B_EMPTY + 21));
            load(I1{}, 13 * RT);
            wgmma_wait<1>();
            cvt(pk, 22);
            mma_e1(I0{});
            store(pk, 22);
            wgmma_wait<1>();
            cvt(pk, 23);
            mma_e1(I1{});
            auto mma_h = [&](auto VC, int hh) {
                mma_d1(VC, 2 * hh, 1);
                mma_d1(VC, 2 * hh + 1, 1);
                wgmma_commit();
            };
            mma_h(I2{}, 0);
            store(pk, 23);
            wgmma_wait<1>();
            if (l0) mbar_arrive(BAR(B_ZRDY));
            TS(2);
            za[6] = za[7] = 0u;
            cvt(pk, 24);
            cvt(p2, 25);
#pragma unroll
            for (int i = 0; i < 6; i++) za[i] |= p2[7] & (ln >> 5);
            constexpr uint64_t d1 = make_desc(SB0 + OFF_SEF, 256, 128, 0), d2 = make_desc(SB0 + OFF_SEF + 1024, 512, 128, 0);
            float h[8], o[16];
#pragma unroll
            for (int i = 0; i < 16; i++) asm volatile("" : "=f"(o[i]), "=f"(h[i & 7]));
            wgmma_fence();
            wgmma_m64n16k16_rs<0>(h, za, d1);
            wgmma_m64n16k16_rs<1>(h, za + 4, d1 + 32);
            wgmma_commit();
            mma_h(I2{}, 1);
            mma_d(I3{}, 1);
            wgmma_wait<2>();
            const uint32_t ha0 = pack_bf16(gelu2(h[0]), gelu2(h[1])), ha1 = pack_bf16(gelu2(h[2]), gelu2(h[3])), ha2 = pack_bf16(gelu2(h[4]), gelu2(h[5])),
                           ha3 = pack_bf16(gelu2(h[6]), gelu2(h[7]));
            wgmma_fence();
            wgmma_m64n32k16_rs<2>(o, ha0, ha1, ha2, ha3, d2);
            wgmma_commit();
            wgmma_wait<2>();
            if (l0) mbar_arrive(BAR(B_EMPTY + 22));
            READY(24);
            mma_d(I0{}, 1);
            READY(25);
            store(pk, 24);
            store(p2, 25);
            wgmma_wait<1>();
            if (l0) mbar_arrive(BAR(B_EMPTY + 23));
            mma_d(I1{}, 1);
#pragma unroll
            for (int i = 0; i < 2; i++) {
                uint32_t a[4];
#pragma unroll
                for (int k = 0; k < 4; k++) a[k] = pack_bf16(fmaf(tanh_fast(o[8 * i + 2 * k]), 0.5f, 0.5f), fmaf(tanh_fast(o[8 * i + 2 * k + 1]), 0.5f, 0.5f));
                sts128(sb + OFF_AP + i * 2048 + warp * 512 + ln * 16, a[0], a[1], a[2], a[3]);
            }
            __syncwarp();
            if (l0) mbar_arrive(BAR(B_EWRDY));
            wgmma_wait<1>();
            if (l0) mbar_arrive(BAR(B_EMPTY + 24));
            TS(3);
        }
        {
            wgmma_wait<0>();
            if (l0) mbar_arrive(BAR(B_EMPTY + 25));
            uint32_t hw[32];
#pragma unroll
            for (int i = 0; i < 32; i++) asm volatile("cvt.rn.bf16x2.f32 %0, %1, %2;" : "=r"(hw[i]) : "f"(acc[2 * i + 1]), "f"(acc[2 * i]));
            asm volatile("setmaxnreg.dec.sync.aligned.u32 %0;" ::"n"(R_DEEP2));
            TS(4);
            float o[4] = {0.f, 0.f, 0.f, 0.f};
            int l2;
            asm volatile("mov.u32 %0, %%laneid;" : "=r"(l2));
#pragma unroll
            for (int it = 0; it < 8; it++) {
                uint32_t b0, b1;
                asm volatile("ld.shared.v2.u32 {%0,%1}, [%2];" : "=r"(b0), "=r"(b1) : "r"(sb + OFF_W2 + 8 * (l2 & 3) + it * 32));
                mma16816(o, gelu2p(hw[4 * it]), gelu2p(hw[4 * it + 1]), gelu2p(hw[4 * it + 2]), gelu2p(hw[4 * it + 3]), b0, b1);
            }
            send_partial(sb, rank * 3, warp, l2 >> 2, l2 & 3, 0.5f * o[0], 0.5f * o[2]);
        }
        TS(5);
    } else {
        const int wgc = (warp >> 2) - 1, w4 = warp & 3;
        const char* so = (const char*)table + 16 * (lane & 7);
        auto rp = [&](uint32_t i) { return row_ptr(so, i); };
        const uint32_t d0 = opq(sb + OFF_RT + b * 128 + (((lane ^ b) & 7) << 4)), d1 = opq((d0 ^ 64) + 6 * RT);
        uint32_t c0;
        auto until = [&](int f) {
            for (;;) {
                uint32_t c;
                asm volatile("mov.u32 %0, %%clock;" : "=r"(c)::"memory");
                if (c - c0 >= f * 300) break;
                __nanosleep(32);
            }
        };
        {
            const int ia[4] = {i0a.x, i0a.y, i1a.x, i1a.y}, ib[4] = {i0b.x, i0b.y, i1b.x, i1b.y};
            static_for<0, NFIRST>([&](auto FC) {
                constexpr int f = decltype(FC)::value, o = (f >> 1) * RT;
                if (f) until(f);
                cp_async16(((f & 1) ? d1 : d0) + o, rp(ia[f]));
                cp_async16(((f & 1) ? d1 : d0) + o + 4096, rp(ib[f]));
                cp_async_mbar_arrive_noinc(BAR(((f & 1) ? B_PAIR : B_F) + (f >> 1)));
                if (f == 0) asm volatile("mov.u32 %0, %%clock;" : "=r"(c0)::"memory");
            });
            if (wgc == 0) TS(6);
        }
        asm volatile("setmaxnreg.inc.sync.aligned.u32 %0;" ::"n"(R_CR1));
        uint32_t M[8][12], y[4][2];
        {
            const uint32_t pa = opq(sb + OFF_RT + (t & 1) * 6 * RT + (16 * w4 + g) * 128 + (((4 * rank + 2 * wgc) ^ g ^ (4 * (t & 1))) << 4)), t1 = opq(t >> 1);
            const uint32_t ia = opq(sb + OFF_IDX + b * NF * 4);
#pragma unroll
            for (int i = 0; i < 96; i++) asm volatile("" : "=r"(M[i / 12][i % 12]));
            mbar_wait(BAR(B_IDX), 0);
            uint32_t x[13][4];
#pragma unroll
            for (int p = 2; p < 13; p++)
                asm volatile("ld.shared.v2.u32 {%0,%1}, [%4];\nld.shared.v2.u32 {%2,%3}, [%4 + 3328];" : "=r"(x[p][0]), "=r"(x[p][2]), "=r"(x[p][1]), "=r"(x[p][3]) : "r"(ia + p * 8));
            const uint32_t pb = opq(pa ^ 16);
            auto conv = [&](int G) {
#pragma unroll
                for (int i = 0; i < 16; i++) {
                    uint32_t &u = M[i >> 1][4 * G + 2 * (i & 1)], &v = M[i >> 1][4 * G + 2 * (i & 1) + 1];
                    asm volatile("{\n.reg .b32 t;\nprmt.b32 t, %0, %1, 0x5410;\nprmt.b32 %1, %0, %1, 0x7632;\nmov.b32 %0, t;\n}\n" : "+r"(u), "+r"(v));
                }
#pragma unroll
                for (int i = 0; i < 8; i++)
                    asm volatile("{\n.reg .pred p;\nsetp.eq.u32 p, %5, 2;\n@p st.shared.v4.u32 [%4], {%0,%1,%2,%3};\n}\n" ::"r"(M[i & 4][4 * G + (i & 3)]), "r"(M[(i & 4) + 1][4 * G + (i & 3)]),
                                 "r"(M[(i & 4) + 2][4 * G + (i & 3)]), "r"(M[(i & 4) + 3][4 * G + (i & 3)]), "r"(pa), "r"(t1));
            };
            auto gather = [&](auto PC) {
                constexpr int p = decltype(PC)::value;
                constexpr uint32_t o1 = (p < 12 ? p : 7) * RT;
                if (p < 6) until(2 * p);
                cp_async16(d0 + p * RT, rp(x[p][0]));
                cp_async16(d0 + p * RT + 4096, rp(x[p][1]));
                if (p < 6) until(2 * p + 1);
                cp_async16(d1 + o1, rp(x[p][2]));
                cp_async16(d1 + o1 + 4096, rp(x[p][3]));
                cp_async_mbar_arrive_noinc(BAR(B_PAIR + p));
            };
            auto pick = [&](auto QC) {
                constexpr int q = decltype(QC)::value, c = 4 * (q >> 2) + ((q >> 1) & 1);
#pragma unroll
                for (int i = 0; i < 4; i++)
                    asm volatile("{\n.reg .pred p;\nsetp.eq.u32 p, %5, %6;\n@p ld.shared.v4.u32 {%0,%1,%2,%3}, [%4];\n}\n"
                                 : "+r"(M[2 * (i & 2)][c + 2 * (i & 1)]), "+r"(M[2 * (i & 2) + 1][c + 2 * (i & 1)]), "+r"(M[2 * (i & 2) + 2][c + 2 * (i & 1)]),
                                   "+r"(M[2 * (i & 2) + 3][c + 2 * (i & 1)])
                                 : "r"(((i & 2) ? pb : pa) + q * RT + (i & 1) * 1024), "r"(t1), "n"(q & 1));
                __syncwarp();
                if (elect_one()) mbar_arrive(BAR(B_W + 2 * q + 1 + (q == 0)));
                if (q == 4 || q == 8) conv(q / 4 - 1);
            };
#define IC(x) std::integral_constant<int, x>{}
            gather(IC(2));
            gather(IC(3));
            static_for<0, 3>([&](auto QC) {
                constexpr int q = decltype(QC)::value;
                mbar_wait(BAR(B_PAIR + q), 0);
                pick(QC);
                if constexpr (q < 2) gather(IC(q + 4));
            });
            static_for<3, 12>([&](auto QC) {
                constexpr int q = decltype(QC)::value, p = q < 9 ? q + 3 : q == 10 ? 12 : 0;
                mbar_wait(BAR(B_EMPTY + 2 * q - 6 + (q == 3)), 0);
                mbar_wait(BAR(B_PAIR + q), 0);
                if constexpr (p) gather(IC(p));
                pick(QC);
            });
            const uint32_t ta = sb + OFF_RT + 12 * RT + (16 * w4 + g) * 128 + (((4 * rank + 2 * wgc + (t >> 1)) ^ g) << 4) + 8 * (t & 1);
            mbar_wait(BAR(B_PAIR + 12), 0);
#pragma unroll
            for (int k = 0; k < 4; k++) asm volatile("ld.shared.v2.u32 {%0,%1}, [%2];" : "=r"(y[k][0]), "=r"(y[k][1]) : "r"(((k & 1) ? (ta ^ 64) + RT : ta) + (k >> 1) * 1024));
            __syncwarp();
            if (elect_one()) mbar_arrive(BAR(B_W + 25));
            conv(2);
        }
        uint32_t TL[4][2];
        uint32_t ap[8], a0, a1;
        mbar_wait(BAR(B_CFULL), 0);
        mbar_wait(BAR(B_EWRDY), 0);
        if (wgc == 0) TS(60);
        asm volatile("setmaxnreg.inc.sync.aligned.u32 %0;" ::"n"(R_CR2));
        if (wgc == 0) TS(61);
        {
            int l2;
            asm volatile("mov.u32 %0, %%laneid;" : "=r"(l2));
            const int r = l2 & 7, bh = (l2 >> 3) & 1, ig = l2 >> 4;
            const uint32_t x = sb + OFF_EW + wgc * 256 + (2 * w4 + bh) * 512 + (8 * ig + 4 * (r & 1) + (r >> 1)) * EWP;
            a0 = opq(x);
            a1 = opq(x + (!ig || r == 0 ? 16 : r == 1 ? 13 : 8) * EWP);
#pragma unroll
            for (int i = 0; i < 2; i++) {
                const uint4 v = lds128(sb + OFF_AP + i * 2048 + w4 * 512 + l2 * 16);
                ap[4 * i] = v.x, ap[4 * i + 1] = v.y, ap[4 * i + 2] = v.z, ap[4 * i + 3] = v.w;
            }
        }
        constexpr uint64_t dt = make_desc(SB0 + OFF_TW, 512, 128, 0), dqc = make_desc(SB0 + OFF_ID, 128, 128, 0);
        const uint64_t dq = uni64(dqc + (sb >> 28));
        const uint64_t desc = dt + wgc * (CHUNK >> 4);
        auto dsc = [&](int e, int pq) { return desc + ((CPOS >> (4 * (e >> 1))) & 7) * (2 * CHUNK >> 4) + ((e & 1) * 2 + pq) * (TILE >> 4); };
        float S[4], accP[16], accQ[16];
#pragma unroll
        for (int i = 0; i < 16; i++) asm volatile("" : "=f"(accP[i]), "=f"(accQ[i]));
        uint32_t A0[8], A1[8], Aq[8], w[8];
        u_lda(A0, a0, a1);
        u_lda(A1, a0 + 16, a1 + 16);
#pragma unroll
        for (int k = 0; k < 8; k++) asm volatile("prmt.b32 %0, %1, %2, %3;" : "=r"(TL[k >> 1][k & 1]) : "r"(y[2 * (k & 1)][k >> 2]), "r"(y[2 * (k & 1) + 1][k >> 2]), "r"(0x5410 + 0x2222 * ((k >> 1) & 1)));
#pragma unroll
        for (int i = 0; i < 4; i++) asm volatile("" : "=f"(S[i]));
#pragma unroll
        for (int k = 0; k < 8; k++) Aq[k] = hmul2_bf16(A0[k], ap[k]);
        wgmma_fence();
        u_mma(accP, A0, dsc(0, 0));
        wgmma_commit();
        u_mma(accQ, Aq, dsc(0, 1));
        wgmma_commit();
        if (wgc == 0) TS(62);
        auto pack8 = [&](uint32_t (&d)[8], const float (&a)[16]) {
#pragma unroll
            for (int k = 0; k < 8; k++) asm volatile("cvt.rn.bf16x2.f32 %0, %1, %2;" : "=r"(d[k]) : "f"(a[2 * k + 1]), "f"(a[2 * k]));
        };
        static_for<0, 8>([&](auto PC) {
            constexpr int p = decltype(PC)::value, e = 2 * p;
            auto mw = [&](int s, int k) { return k < 6 ? M[p][2 * k + s] : TL[(e + s) & 3][k - 6]; };
            uint32_t tp[8], tq[8];
            wgmma_wait<1>();
            pack8(tp, accP);
            wgmma_fence();
            u_mma(accP, A1, dsc(e + 1, 0));
            if (p) {
                wgmma_m64n8k16_rs(S, w, dq, p > 1);
                wgmma_m64n8k16_rs(S, w + 4, dq, 1);
            }
            wgmma_commit();
            if (p < 7) u_lda(A0, a0 + 16 * e + 32, a1 + 16 * e + 32);
            wgmma_wait<1>();
            pack8(tq, accQ);
#pragma unroll
            for (int k = 0; k < 8; k++) Aq[k] = hmul2_bf16(A1[k], ap[k]);
            wgmma_fence();
            u_mma(accQ, Aq, dsc(e + 1, 1));
            wgmma_commit();
#pragma unroll
            for (int k = 0; k < 8; k++) tq[k] = hfma2_bf16(tq[k], ap[k], tp[k]);
            if (p == 0 || p == 2 || p == 5) mbar_wait(BAR(B_CFULL + 1 + p / 2), 0);
            wgmma_wait<1>();
            pack8(tp, accP);
            if (p < 7) {
                wgmma_fence();
                u_mma(accP, A0, dsc(e + 2, 0));
                wgmma_commit();
                u_lda(A1, a0 + 16 * e + 48, a1 + 16 * e + 48);
            }
#pragma unroll
            for (int k = 0; k < 8; k++) w[k] = hmul2_bf16(tq[k], mw(0, k));
            wgmma_wait<(p < 7)>();
            if (p == 0 && elect_one()) mbar_arrive(BAR(B_CDONE));
            pack8(tq, accQ);
            if (p < 7) {
#pragma unroll
                for (int k = 0; k < 8; k++) Aq[k] = hmul2_bf16(A0[k], ap[k]);
                wgmma_fence();
                u_mma(accQ, Aq, dsc(e + 2, 1));
                wgmma_commit();
            }
#pragma unroll
            for (int k = 0; k < 8; k++) w[k] = hfma2_bf16(hfma2_bf16(tq[k], ap[k], tp[k]), mw(1, k), w[k]);
        });
        int tid2;
        asm volatile("mov.u32 %0, %%laneid;" : "=r"(tid2));
        wgmma_fence();
        wgmma_m64n8k16_rs(S, w, dq, 1);
        wgmma_m64n8k16_rs(S, w + 4, dq, 1);
        wgmma_commit();
        wgmma_wait<0>();
        send_partial(sb, rank * 3 + 1 + wgc, w4, tid2 >> 2, tid2 & 3, S[0], S[2]);
        if (wgc == 0) TS(14);
    }
#undef BAR
}

typedef CUresult (*PFN_encodeTiled)(CUtensorMap*, CUtensorMapDataType, cuuint32_t, void*, const cuuint64_t*, const cuuint64_t*,
                                    const cuuint32_t*, const cuuint32_t*, CUtensorMapInterleave, CUtensorMapSwizzle,
                                    CUtensorMapL2promotion, CUtensorMapFloatOOBfill);

}

extern "C" void kernel_launch(void* const* d_in, const int* in_sizes, int n_in, void* d_out, int out_size) {
    const int* idx = (const int*)d_in[0];
    const __nv_bfloat16* table = (const __nv_bfloat16*)d_in[1];
    const __nv_bfloat16* se_w1 = (const __nv_bfloat16*)d_in[2];
    const __nv_bfloat16* se_w2 = (const __nv_bfloat16*)d_in[3];
    const __nv_bfloat16* w_bi = (const __nv_bfloat16*)d_in[4];
    const __nv_bfloat16* w_cross = (const __nv_bfloat16*)d_in[5];
    const __nv_bfloat16* w_deep1 = (const __nv_bfloat16*)d_in[6];
    const __nv_bfloat16* w_deep2 = (const __nv_bfloat16*)d_in[7];
    __nv_bfloat16* out = (__nv_bfloat16*)d_out;

    static PFN_encodeTiled enc = nullptr;
    if (!enc) {
        void* fn = nullptr;
        cudaDriverEntryPointQueryResult qres;
        cudaGetDriverEntryPoint("cuTensorMapEncodeTiled", &fn, cudaEnableDefault, &qres);
        enc = (PFN_encodeTiled)fn;
        cudaFuncSetAttribute(fused_kernel, cudaFuncAttributeMaxDynamicSharedMemorySize, SMEM);
    }
    CUtensorMap tm;
    {
        cuuint64_t gdim[3] = {64, (cuuint64_t)(NF * ND), 4};
        cuuint64_t gstr[2] = {(cuuint64_t)NH * 2, 128};
        cuuint32_t box[3] = {64, 64, 2};
        cuuint32_t estr[3] = {1, 1, 1};
        enc(&tm, CU_TENSOR_MAP_DATA_TYPE_BFLOAT16, 3, (void*)w_deep1, gdim, gstr, box, estr, CU_TENSOR_MAP_INTERLEAVE_NONE,
            CU_TENSOR_MAP_SWIZZLE_128B, CU_TENSOR_MAP_L2_PROMOTION_L2_256B, CU_TENSOR_MAP_FLOAT_OOB_FILL_NONE);
    }
    fused_kernel<<<128, 512, SMEM>>>(idx, table, w_deep1, w_bi, w_deep2, w_cross, se_w1, se_w2, out, tm);
}
```

```cpp
#include <cuda_runtime.h>
#include <cuda_bf16.h>
#include <cuda.h>
#include <stdint.h>
#include <type_traits>
#include <utility>

#define R_DEEP 216
#define R_CR1 136
#define R_CR2 216
#define R_DEEP2 56
#define R_PROD 24

namespace {

constexpr int NF = 26, ND = 64, NH = 256, NFR = 13;

#define TS(slot)
#define TSL(slot)

__device__ __forceinline__ uint32_t smem_u32(const void* p) { return (uint32_t)__cvta_generic_to_shared(p); }
__device__ __forceinline__ void mbar_init(uint32_t bar, uint32_t cnt) {
    asm volatile("mbarrier.init.shared::cta.b64 [%0], %1;" ::"r"(bar), "r"(cnt));
}
__device__ __forceinline__ void mbar_expect_tx(uint32_t bar, uint32_t bytes) {
    asm volatile("mbarrier.arrive.expect_tx.shared::cta.b64 _, [%0], %1;" ::"r"(bar), "r"(bytes) : "memory");
}
__device__ __forceinline__ void mbar_arrive(uint32_t bar) {
    asm volatile("mbarrier.arrive.shared::cta.b64 _, [%0];" ::"r"(bar) : "memory");
}
__device__ __forceinline__ void mbar_wait(uint32_t bar, uint32_t parity) {
    asm volatile(
        "{\n"
        ".reg .pred p;\n"
        "WAIT_%=:\n"
        "mbarrier.try_wait.parity.shared::cta.b64 p, [%0], %1;\n"
        "@p bra.uni DONE_%=;\nbra.uni WAIT_%=;\nDONE_%=:\n"
        "}\n" ::"r"(bar),
        "r"(parity)
        : "memory");
}
__device__ __forceinline__ uint32_t opq(uint32_t x) { return __shfl_xor_sync(0xffffffffu, x, 0); }
__device__ __forceinline__ uint64_t uni64(uint64_t x) {
    uint32_t lo = (uint32_t)x, hi = (uint32_t)(x >> 32);
    asm volatile("shfl.sync.idx.b32 %0, %0, 0, 31, -1;\nshfl.sync.idx.b32 %1, %1, 0, 31, -1;" : "+r"(lo), "+r"(hi));
    return ((uint64_t)hi << 32) | lo;
}
__device__ __forceinline__ bool elect_one() {
    uint32_t r;
    asm volatile("{\n.reg .pred p;\nelect.sync _|p, 0xffffffff;\nselp.u32 %0, 1, 0, p;\n}\n" : "=r"(r));
    return r;
}
__device__ __forceinline__ const void* row_ptr(const void* base, uint32_t i) {
    const void* r;
    asm("mad.wide.u32 %0, %1, 128, %2;" : "=l"(r) : "r"(i), "l"(base));
    return r;
}
__device__ __forceinline__ void mbar_wait_bounded(uint32_t bar, uint32_t parity) {
    asm volatile(
        "{\n"
        ".reg .pred p;\n"
        ".reg .u32 c;\n"
        "mov.u32 c, 0;\n"
        "WAIT_%=:\n"
        "mbarrier.try_wait.parity.shared::cta.b64 p, [%0], %1;\n"
        "@p bra.uni DONE_%=;\n"
        "add.u32 c, c, 1;\n"
        "setp.lt.u32 p, c, 0x400000;\n"
        "@p bra.uni WAIT_%=;\n"
        "trap;\n"
        "DONE_%=:\n"
        "}\n" ::"r"(bar),
        "r"(parity)
        : "memory");
}
__device__ __forceinline__ void cp_async16(uint32_t dst, const void* src) {
    asm volatile("cp.async.cg.shared.global [%0], [%1], 16;" ::"r"(dst), "l"(src) : "memory");
}
__device__ __forceinline__ void cp_async_mbar_arrive_noinc(uint32_t bar) {
    asm volatile("cp.async.mbarrier.arrive.noinc.shared::cta.b64 [%0];" ::"r"(bar) : "memory");
}
__device__ __forceinline__ void tma_load_3d(uint32_t dst, const void* tmap, int c0, int c1, int c2, uint32_t bar) {
    asm volatile(
        "cp.async.bulk.tensor.3d.shared::cluster.global.mbarrier::complete_tx::bytes [%0], [%1, {%3, %4, %5}], [%2];" ::"r"(dst),
        "l"(tmap), "r"(bar), "r"(c0), "r"(c1), "r"(c2)
        : "memory");
}
__device__ __forceinline__ void bulk_load(uint32_t dst, const void* src, uint32_t bytes, uint32_t bar) {
    asm volatile("cp.async.bulk.shared::cluster.global.mbarrier::complete_tx::bytes [%0], [%1], %2, [%3];" ::"r"(dst), "l"(src), "r"(bytes),
                 "r"(bar)
                 : "memory");
}
__device__ __forceinline__ void fence_proxy_async() { asm volatile("fence.proxy.async.shared::cta;" ::: "memory"); }
__device__ __forceinline__ void wgmma_fence() { asm volatile("wgmma.fence.sync.aligned;" ::: "memory"); }
__device__ __forceinline__ void wgmma_commit() { asm volatile("wgmma.commit_group.sync.aligned;" ::: "memory"); }
template <int N> __device__ __forceinline__ void wgmma_wait() { asm volatile("wgmma.wait_group.sync.aligned %0;" ::"n"(N) : "memory"); }

__device__ __forceinline__ void ldsm_x4(uint32_t addr, uint32_t& r0, uint32_t& r1, uint32_t& r2, uint32_t& r3) {
    asm volatile("ldmatrix.sync.aligned.m8n8.x4.shared.b16 {%0,%1,%2,%3}, [%4];" : "=r"(r0), "=r"(r1), "=r"(r2), "=r"(r3) : "r"(addr));
}
__device__ __forceinline__ void ldsm_x4_t(uint32_t addr, uint32_t& r0, uint32_t& r1, uint32_t& r2, uint32_t& r3) {
    asm volatile("ldmatrix.sync.aligned.m8n8.x4.trans.shared.b16 {%0,%1,%2,%3}, [%4];" : "=r"(r0), "=r"(r1), "=r"(r2), "=r"(r3) : "r"(addr));
}
__device__ __forceinline__ void stsm_x4_t(uint32_t addr, uint32_t r0, uint32_t r1, uint32_t r2, uint32_t r3) {
    asm volatile("stmatrix.sync.aligned.m8n8.x4.trans.shared.b16 [%0], {%1,%2,%3,%4};" ::"r"(addr), "r"(r0), "r"(r1), "r"(r2), "r"(r3) : "memory");
}
__device__ __forceinline__ uint4 lds128(uint32_t addr) {
    uint4 v;
    asm volatile("ld.shared.v4.u32 {%0,%1,%2,%3}, [%4];" : "=r"(v.x), "=r"(v.y), "=r"(v.z), "=r"(v.w) : "r"(addr));
    return v;
}
__device__ __forceinline__ uint32_t lds32(uint32_t addr) {
    uint32_t v;
    asm volatile("ld.shared.u32 %0, [%1];" : "=r"(v) : "r"(addr));
    return v;
}
__device__ __forceinline__ void sts128(uint32_t addr, uint32_t a, uint32_t b, uint32_t c, uint32_t d) {
    asm volatile("st.shared.v4.u32 [%0], {%1,%2,%3,%4};" ::"r"(addr), "r"(a), "r"(b), "r"(c), "r"(d) : "memory");
}
__device__ __forceinline__ void mma16816(float (&c)[4], uint32_t a0, uint32_t a1, uint32_t a2, uint32_t a3, uint32_t b0, uint32_t b1) {
    asm("mma.sync.aligned.m16n8k16.row.col.f32.bf16.bf16.f32 {%0,%1,%2,%3}, {%4,%5,%6,%7}, {%8,%9}, {%0,%1,%2,%3};"
        : "+f"(c[0]), "+f"(c[1]), "+f"(c[2]), "+f"(c[3])
        : "r"(a0), "r"(a1), "r"(a2), "r"(a3), "r"(b0), "r"(b1));
}
__device__ __forceinline__ uint32_t pack_bf16(float lo, float hi) {
    uint32_t r;
    asm("cvt.rn.bf16x2.f32 %0, %1, %2;" : "=r"(r) : "f"(hi), "f"(lo));
    return r;
}
__device__ __forceinline__ uint32_t hmul2_bf16(uint32_t a, uint32_t b) {
    uint32_t r;
    asm("mul.rn.bf16x2 %0, %1, %2;" : "=r"(r) : "r"(a), "r"(b));
    return r;
}
__device__ __forceinline__ float tanh_fast(float x) {
    float r;
    asm("tanh.approx.f32 %0, %1;" : "=f"(r) : "f"(x));
    return r;
}
#define WG_ACC8(c, b) c(acc[b]), c(acc[b + 1]), c(acc[b + 2]), c(acc[b + 3]), c(acc[b + 4]), c(acc[b + 5]), c(acc[b + 6]), c(acc[b + 7])
#define WG_N128(c, sc)                                                                                                              \
    asm volatile(                                                                                                                   \
        "{\n"                                                                                                                       \
        ".reg .pred p;\n"                                                              \
        "setp.ne.b32 p, " sc ", 0;\n"                                                                                               \
        "wgmma.mma_async.sync.aligned.m64n128k16.f32.bf16.bf16 "                                                                    \
        "{%0,%1,%2,%3,%4,%5,%6,%7,%8,%9,%10,%11,%12,%13,%14,%15,"                                                                   \
        "%16,%17,%18,%19,%20,%21,%22,%23,%24,%25,%26,%27,%28,%29,%30,%31,"                                                          \
        "%32,%33,%34,%35,%36,%37,%38,%39,%40,%41,%42,%43,%44,%45,%46,%47,"                                                          \
        "%48,%49,%50,%51,%52,%53,%54,%55,%56,%57,%58,%59,%60,%61,%62,%63},"                                                         \
        " {%64,%65,%66,%67}, %68, p, 1, 1, 1;\n"                                                                                    \
        "}\n"                                                                                                                       \
        : WG_ACC8(c, 0), WG_ACC8(c, 8), WG_ACC8(c, 16), WG_ACC8(c, 24), WG_ACC8(c, 32), WG_ACC8(c, 40), WG_ACC8(c, 48), WG_ACC8(c, 56) \
        : "r"(a[0]), "r"(a[1]), "r"(a[2]), "r"(a[3]), "l"(db), "r"(scv))
__device__ __forceinline__ void wgmma_m64n128k16_rs_tb(float (&acc)[64], const uint32_t (&a)[4], uint64_t db, int scv) {
    WG_N128("+f", "%69");
}
#define WG_N40(c, sc)                                                                         \
    asm volatile(                                                                             \
        "{\n"                                                                                 \
        ".reg .pred p;\n"                        \
        "setp.ne.b32 p, " sc ", 0;\n"                                                         \
        "wgmma.mma_async.sync.aligned.m64n40k16.f32.bf16.bf16 "                               \
        "{%0,%1,%2,%3,%4,%5,%6,%7,%8,%9,%10,%11,%12,%13,%14,%15,%16,%17,%18,%19},"            \
        " {%20,%21,%22,%23}, %24, p, 1, 1, 1;\n"                                              \
        "}\n"                                                                                 \
        : WG_ACC8(c, 0), WG_ACC8(c, 8), c(acc[16]), c(acc[17]), c(acc[18]), c(acc[19])        \
        : "r"(a[0]), "r"(a[1]), "r"(a[2]), "r"(a[3]), "l"(db))
template <int SC>
__device__ __forceinline__ void wgmma_m64n40k16_rs_tb(float (&acc)[20], const uint32_t (&a)[4], uint64_t db) {
    if constexpr (SC == 1) WG_N40("+f", "1");
    else if constexpr (SC == 2) WG_N40("+f", "0");
    else WG_N40("=f", "0");
}
#define WG_N32(c, sc)                                                   \
    asm volatile(                                                       \
        "{\n"                                                           \
        ".reg .pred p;\n"           \
        "setp.ne.b32 p, " sc ", 0;\n"                                   \
        "wgmma.mma_async.sync.aligned.m64n32k16.f32.bf16.bf16 "         \
        "{%0,%1,%2,%3,%4,%5,%6,%7,%8,%9,%10,%11,%12,%13,%14,%15},"      \
        " {%16,%17,%18,%19}, %20, p, 1, 1, 0;\n"                        \
        "}\n"                                                           \
        : WG_ACC8(c, 0), WG_ACC8(c, 8)                                  \
        : "r"(a0), "r"(a1), "r"(a2), "r"(a3), "l"(db))
template <int SC>
__device__ __forceinline__ void wgmma_m64n32k16_rs(float (&acc)[16], uint32_t a0, uint32_t a1, uint32_t a2, uint32_t a3, uint64_t db) {
    if constexpr (SC == 1) WG_N32("+f", "1");
    else if constexpr (SC == 2) WG_N32("+f", "0");
    else WG_N32("=f", "0");
}

__host__ __device__ constexpr uint64_t make_desc(uint32_t addr, uint32_t lbo_bytes, uint32_t sbo_bytes, uint32_t swz) {
    uint64_t d = 0;
    d |= (uint64_t)((addr & 0x3FFFF) >> 4);
    d |= (uint64_t)((lbo_bytes >> 4) & 0x3FFF) << 16;
    d |= (uint64_t)((sbo_bytes >> 4) & 0x3FFF) << 32;
    d |= (uint64_t)swz << 62;
    return d;
}
__device__ __forceinline__ uint32_t ldg_u16(const __nv_bfloat16* p) { return (uint32_t)__ldg(reinterpret_cast<const unsigned short*>(p)); }
template <int N, class F, int... I>
__device__ __forceinline__ void static_for_impl(F&& f, std::integer_sequence<int, I...>) {
    (f(std::integral_constant<int, N + I>{}), ...);
}
template <int B, int E, class F>
__device__ __forceinline__ void static_for(F&& f) {
    static_for_impl<B>(f, std::make_integer_sequence<int, E - B>{});
}

__device__ __forceinline__ uint32_t hfma2_bf16(uint32_t a, uint32_t b, uint32_t c) {
    uint32_t r;
    asm("fma.rn.bf16x2 %0, %1, %2, %3;" : "=r"(r) : "r"(a), "r"(b), "r"(c));
    return r;
}
__device__ __forceinline__ float gelu2(float x) {
    const float k0 = 0.7978845608028654f, k01 = 0.7978845608028654f * 0.044715f;
    return fmaf(x, tanh_fast(x * fmaf(x * x, k01, k0)), x);
}
__device__ __forceinline__ uint32_t gelu2p(uint32_t x) {
    uint32_t t;
    const uint32_t u = hmul2_bf16(x, hfma2_bf16(hmul2_bf16(x, x), 0x3D123D12u, 0x3F4C3F4Cu));
    asm("tanh.approx.bf16x2 %0, %1;" : "=r"(t) : "r"(u));
    return hfma2_bf16(x, t, x);
}
__device__ __forceinline__ void wgmma_m64n8k16_rs(float (&acc)[4], const uint32_t* a, uint64_t db, int sc) {
    asm volatile("{\n.reg .pred p;\nsetp.ne.b32 p, %9, 0;\nwgmma.mma_async.sync.aligned.m64n8k16.f32.bf16.bf16 {%0,%1,%2,%3}, {%4,%5,%6,%7}, %8, p, 1, 1, 0;\n}\n"
                 : "+f"(acc[0]), "+f"(acc[1]), "+f"(acc[2]), "+f"(acc[3])
                 : "r"(a[0]), "r"(a[1]), "r"(a[2]), "r"(a[3]), "l"(db), "r"(sc));
}

template <int SC>
__device__ __forceinline__ void wgmma_m64n16k16_rs(float (&acc)[8], const uint32_t* a, uint64_t db) {
    asm volatile("{\n.reg .pred p;\nsetp.ne.b32 p, %13, 0;\nwgmma.mma_async.sync.aligned.m64n16k16.f32.bf16.bf16 {%0,%1,%2,%3,%4,%5,%6,%7}, {%8,%9,%10,%11}, %12, p, 1, 1, 0;\n}\n"
                 : WG_ACC8("+f", 0)
                 : "r"(a[0]), "r"(a[1]), "r"(a[2]), "r"(a[3]), "l"(db), "n"(SC));
}

constexpr int SB0 = 1024;
constexpr int SLOT = 4096;
constexpr int EWP = SLOT + 16;
constexpr int OFF_EW = 608;
constexpr int OFF_RT = 1024;
constexpr int RT = 8192;
constexpr int OFF_TW = OFF_RT + 13 * RT;
constexpr int HS_BYTES = 16384;
constexpr int OFF_RING = OFF_RT + 19 * RT;
constexpr int OFF_WBI = OFF_RT + 18 * RT;
constexpr int OFF_IDX = OFF_RT + 17 * RT;
constexpr int OFF_SEF = OFF_RING + 4 * HS_BYTES;
constexpr int OFF_AP = OFF_SEF + 2048;
constexpr int OFF_W2 = 0;
constexpr int OFF_DP = OFF_AP + 4096;
constexpr int OFF_ID = OFF_DP + 6 * 32 * 4;
constexpr int OFF_BAR = OFF_ID + 256;
constexpr int TILE = 2048;
constexpr int CHUNK = 4 * TILE;
constexpr int NCHUNK = 16;
constexpr int CPOS = 0x16504321;
static_assert(OFF_TW + 14 * CHUNK == OFF_SEF && OFF_EW + 25 * EWP + SLOT <= OFF_TW, "layout");
static_assert(OFF_RING % 1024 == 0 && OFF_WBI % 1024 == 0 && OFF_ID % 128 == 0, "align");
constexpr int B_CFULL = 0,
              B_F = 4,
              B_W = 16,
              B_EMPTY = 48, B_ZRDY = B_EMPTY + NF, B_CDONE = B_ZRDY + 1,
              B_EWRDY = B_CDONE + 2, B_PAIR = 80,
              B_IDX = B_PAIR + 13, B_FIN = B_PAIR + 14;
constexpr int OFF_TS = OFF_BAR + 768;
constexpr int SMEM = OFF_TS + 512;
static_assert(SMEM <= 232448, "smem");
constexpr int NFIRST = 4;
constexpr int JIT = 4;
constexpr int NUNIT = 128;

__device__ __align__(1024) uint8_t g_wt[2 * NCHUNK * CHUNK];
__device__ unsigned int g_cnt;

__device__ __forceinline__ void u_lda(uint32_t (&A)[8], uint32_t a0, uint32_t a1) {
    ldsm_x4_t(a0, A[0], A[1], A[2], A[3]);
    ldsm_x4_t(a1, A[4], A[5], A[6], A[7]);
}
__device__ __forceinline__ void u_mma(float (&acc)[16], const uint32_t (&A)[8], uint64_t desc) {
    wgmma_m64n32k16_rs<2>(acc, A[0], A[1], A[2], A[3], desc);
    wgmma_m64n32k16_rs<1>(acc, A[4], A[5], A[6], A[7], desc + 64);
}
__device__ __forceinline__ void send_partial(uint32_t sb, int src, int w4, int g, int t, float v0, float v1) {
    asm volatile("barrier.cluster.wait.acquire.aligned;" ::: "memory");
    if (t < 2) {
        uint32_t rb;
        asm volatile("mapa.shared::cluster.u32 %0, %1, %2;" : "=r"(rb) : "r"(sb), "r"(w4 >> 1));
        asm volatile("st.async.weak.shared::cluster.mbarrier::complete_tx::bytes.f32 [%0], %1, [%2];" ::"r"(rb + OFF_DP + (src * 32 + (w4 & 1) * 16 + 8 * t + g) * 4),
                     "f"(t ? v1 : v0), "r"(rb + OFF_BAR + B_FIN * 8)
                     : "memory");
    }
}

__global__ void __cluster_dims__(2, 1, 1) __launch_bounds__(512, 1)
fused_kernel(const int* __restrict__ idx, const __nv_bfloat16* __restrict__ table, const __nv_bfloat16* __restrict__ w1, const __nv_bfloat16* __restrict__ w_bi,
             const __nv_bfloat16* __restrict__ w2, const __nv_bfloat16* __restrict__ w_cross, const __nv_bfloat16* __restrict__ se_w1,
             const __nv_bfloat16* __restrict__ se_w2, __nv_bfloat16* __restrict__ out, const __grid_constant__ CUtensorMap tmW1) {
    extern __shared__ __align__(1024) uint8_t smem_raw[];
    const int tid = threadIdx.x, b = (tid >> 3) & 31;
    const int pb0 = (blockIdx.x >> 1) * 64;
    int2 i0a, i0b, i1a, i1b;
    asm volatile("ld.global.nc.v2.u32 {%0,%1}, [%8];\nld.global.nc.v2.u32 {%2,%3}, [%8 + 3328];\nld.global.nc.v2.u32 {%4,%5}, [%8 + 8];\nld.global.nc.v2.u32 {%6,%7}, [%8 + 3336];"
                 : "=r"(i0a.x), "=r"(i0a.y), "=r"(i0b.x), "=r"(i0b.y), "=r"(i1a.x), "=r"(i1a.y), "=r"(i1b.x), "=r"(i1b.y)
                 : "l"(idx + (pb0 + b) * NF));
    const uint32_t sb = __shfl_sync(0xffffffffu, smem_u32(smem_raw), 0);
    const uint32_t bars = sb + OFF_BAR;
#define BAR(i) (bars + (i) * 8)
    const int warp = __shfl_sync(0xffffffffu, tid >> 5, 0), lane = tid & 31, g = lane >> 2, t = lane & 3;
    const int rank = blockIdx.x & 1;
    if (tid == 0) TS(0);
    if (elect_one()) {
        mbar_init(BAR(B_PAIR + warp), warp < 13 ? 256 + (warp == 10) : 1);
        if (warp >= 13) {
            asm volatile("fence.mbarrier_init.release.cluster;" ::: "memory");
            mbar_expect_tx(BAR(B_PAIR + warp), warp == 13 ? 64 * NF * 4 : 6 * 32 * 4);
            if (warp == 13) bulk_load(sb + OFF_IDX, idx + pb0 * NF, 64 * NF * 4, BAR(B_IDX));
        }
        if (warp == 6) asm volatile("cp.async.bulk.prefetch.L2.global [%0], %1;" ::"l"((const char*)w1 + 4 * 32768 + blockIdx.x * 5632), "n"(5632) : "memory");
        mbar_init(BAR(16 + warp), ((0xAAAC >> warp) & 1) ? 9 : 1);
        mbar_init(BAR(32 + warp), (warp & 1) ? 9 : 1);
        mbar_init(BAR(48 + warp), 4);
        mbar_init(BAR(64 + warp), warp == B_CDONE - 64 ? 8 : 4);
        if (warp < 6) mbar_init(BAR(warp), warp < 4 ? (0x2321 >> (4 * warp)) & 3 : 256);
        asm volatile("fence.mbarrier_init.release.cluster;" ::: "memory");
    }
    __syncthreads();
    asm volatile("barrier.cluster.arrive.relaxed.aligned;" ::: "memory");
    if (tid == 0) TS(1);

    if (warp >= 12) {
        asm volatile("setmaxnreg.dec.sync.aligned.u32 %0;" ::"n"(R_PROD));
        if ((sb & 0xFFFFFFu) != SB0) __trap();
        if (warp == 12) {
#pragma unroll 1
            for (int f = 0; f < NF; f++) {
                if (f >= 4) mbar_wait_bounded(BAR(B_EMPTY + f - 4), 0);
                TSL(80 + f);
                if (elect_one()) {
                    mbar_expect_tx(BAR(B_W + f), HS_BYTES);
                    tma_load_3d(sb + OFF_RING + ((f + 2) & 3) * HS_BYTES, &tmW1, 0, f * 64, rank * 2, BAR(B_W + f));
                }
            }
            asm volatile("barrier.cluster.wait.acquire.aligned;" ::: "memory");
            mbar_wait_bounded(BAR(B_FIN), 0);
            float v = 0.f;
#pragma unroll
            for (int i = 0; i < 6; i++) v += __uint_as_float(lds32(sb + OFF_DP + (i * 32 + lane) * 4));
            out[pb0 + 32 * rank + lane] = __float2bfloat16_rn(v);
            TSL(15);
        } else {
            if (warp == 14) {
#pragma unroll 1
                for (int k = JIT; k < NF; k++) {
                    mbar_wait(BAR(B_PAIR + min((k + 3) >> 1, 12)), 0);
                    mbar_wait(BAR(B_W + k), 0);
                    asm volatile("bar.arrive %0, 160;" ::"r"(4 + (k & 3)) : "memory");
                }
            } else if (warp == 13) {
                const uint32_t sr = sb + OFF_AP;
                {
                    uint32_t v[12];
#pragma unroll
                    for (int i = 0; i < 12; i++) v[i] = lane + 32 * (i >> 1) < NF * NFR / 2 ? __ldg(reinterpret_cast<const uint32_t*>((i & 1) ? se_w2 : se_w1) + lane + 32 * (i >> 1)) : 0u;
#pragma unroll
                    for (int i = 0; i < 12; i++) asm volatile("st.shared.u32 [%0], %1;" ::"r"(sr + lane * 4 + (i >> 1) * 128 + (i & 1) * 1024), "r"(v[i]) : "memory");
                    __syncwarp();
                }
#pragma unroll 1
                for (int q = 0; q < 8; q++) {
                    const int c1 = 8 * (q & 1) + g, o1 = c1 < NFR ? min((8 * (q >> 1) + 2 * t) * NFR + c1, NF * NFR) : NF * NFR;
                    const int c2 = 8 * (q & 3) + ((q & 3) < 3 ? 4 * (g & 1) + (g >> 1) : (g & 1)), o2 = min((8 * (q >> 2) + 2 * t) * NF + c2, NF * NFR);
                    uint32_t y1, y2;
                    asm volatile("{\n.reg .b16 a, b, c, d;\nld.shared.b16 a, [%2];\nld.shared.b16 b, [%2 + 26];\nld.shared.b16 c, [%3 + 1024];\nld.shared.b16 d, [%3 + 1076];\n"
                                 "mov.b32 %0, {a, b};\nmov.b32 %1, {c, d};\n}\n" : "=r"(y1), "=r"(y2) : "r"(sr + 2 * o1), "r"(sr + 2 * o2));
                    asm volatile("st.shared.u32 [%0], %1;\nst.shared.u32 [%0 + 1024], %2;" ::"r"(sb + OFF_SEF + q * 128 + lane * 4), "r"(y1),
                                 "r"(hmul2_bf16(y2, 0x3E803E80u))
                                 : "memory");
                }
                fence_proxy_async();
                __syncwarp();
                TSL(12);
                if (elect_one()) mbar_arrive(BAR(B_PAIR + 10));
            } else {
                {
                    const int pq = blockIdx.x >> 6, js = (blockIdx.x >> 1) & 31;
                    const int j = js < 24 ? (js & 24) + 4 * (js & 1) + ((js >> 1) & 3) : 24 + (js & 1);
                    const bool on = js < 24 || ((js >> 1) & 3) == ((lane >> 2) & 3);
                    const __nv_bfloat16* s = w_cross + ((size_t)(pq * NF) * NF + j) * ND + 32 * rank + lane;
                    uint8_t* d = g_wt + (size_t)rank * NCHUNK * CHUNK + (((lane & 15) >> 1) * 2 + (lane >> 4)) * CHUNK + ((lane & 1) * 2 + pq) * TILE + js * 16;
#pragma unroll 1
                    for (int kh = 0; kh < 2; kh++) {
                        uint32_t x[8];
#pragma unroll
                        for (int k = 0; k < 8; k++)
                            x[k] = (on && (kh == 0 || k < 5)) ? ldg_u16(s + (k + (k & 4)) * NF * ND) | (ldg_u16(s + (k == 4 && kh ? 9 : k + (k & 4) + 4) * NF * ND) << 16) : 0u;
                        *reinterpret_cast<uint4*>(d) = make_uint4(x[0], x[1], x[2], x[3]);
                        *reinterpret_cast<uint4*>(d + 512) = make_uint4(x[4], x[5], x[6], x[7]);
                        s += 16 * NF * ND;
                        d += 1024;
                    }
                    __syncwarp();
                }
                TSL(8);
                if (elect_one()) asm volatile("red.release.gpu.global.inc.u32 [%0], %1;" ::"l"(&g_cnt), "n"(NUNIT + 127) : "memory");
                TSL(9);
                mbar_wait(BAR(B_EMPTY + 6), 0);
                TSL(10);
                unsigned int v;
                do {
                    asm volatile("ld.acquire.gpu.global.u32 %0, [%1];" : "=r"(v) : "l"(&g_cnt) : "memory");
                } while (v < NUNIT);
                asm volatile("fence.proxy.async.global;" ::: "memory");
                __syncwarp();
                if (elect_one()) asm volatile("red.relaxed.gpu.global.inc.u32 [%0], %1;" ::"l"(&g_cnt), "n"(NUNIT + 127) : "memory");
                TSL(11);
                const uint8_t* wsrc = g_wt + (size_t)rank * NCHUNK * CHUNK;
#pragma unroll 1
                for (int k = 0; k < 8; k++) {
                    mbar_wait(BAR(B_EMPTY + 20 + ((0x75493260 >> (4 * k)) & 15)), 0);
                    TSL(30 + k);
                    if (elect_one()) {
                        const uint32_t cf = BAR(B_CFULL + ((0x33222110 >> (4 * k)) & 3));
                        mbar_expect_tx(cf, 2 * CHUNK);
                        bulk_load(sb + OFF_TW + ((CPOS >> (4 * k)) & 7) * 2 * CHUNK, wsrc + k * 2 * CHUNK, 2 * CHUNK, cf);
                    }
                }
            }
            __syncwarp();
            asm volatile("barrier.cluster.wait.acquire.aligned;" ::: "memory");
        }
    } else if (warp < 4) {
        {
            const uint4* wb = reinterpret_cast<const uint4*>(w_bi + (tid >> 2) * 64 + 32 * rank + 8 * t);
            const uint4 wb0 = __ldg(wb), wb1 = __ldg(wb + 256);
            const uint32_t w2v = __ldg(reinterpret_cast<const uint32_t*>(w2) + rank * 64 + (tid & 63));
            sts128(sb + OFF_WBI + (tid & 63) * 128 + ((4 ^ (tid & 7)) << 4), 0x3C803C80u, 0x3C803C80u, 0x3C803C80u, 0x3C803C80u);
            asm volatile("st.shared.u32 [%0], %1;" ::"r"(sb + OFF_ID + (tid & 63) * 4), "r"(0x3F803F80u) : "memory");
            asm volatile("st.shared.u32 [%0], %1;" ::"r"(sb + OFF_W2 + (tid & 56) * 4 + (tid & 3) * 8 + (tid & 4)), "r"(w2v) : "memory");
            const uint32_t wd = sb + OFF_WBI + (tid >> 2) * 128 + ((t ^ (g & 7)) << 4);
            sts128(wd, wb0.x, wb0.y, wb0.z, wb0.w);
            sts128(wd + 4096, wb1.x, wb1.y, wb1.z, wb1.w);
            fence_proxy_async();
        }
        asm volatile("setmaxnreg.inc.sync.aligned.u32 %0;" ::"n"(R_DEEP));
        asm volatile("bar.sync 1, 128;" ::: "memory");
        TS(7);
        float acc[64];
        float e2[2][20];
#pragma unroll
        for (int i = 0; i < 64; i++) asm volatile("" : "=f"(acc[i]));
#pragma unroll
        for (int i = 0; i < 20; i++) asm volatile("" : "=f"(e2[0][i]), "=f"(e2[1][i]));
        uint32_t A[4][4][4];
        constexpr uint64_t dr = make_desc(SB0 + OFF_RING, 8192, 1024, 1), dwc = make_desc(SB0 + OFF_WBI, 4096, 1024, 1);
        const uint64_t dw = uni64(dwc + (sb >> 28));
        const uint32_t sa = opq((lane >> 4) * 128 + (2 * warp + ((lane >> 3) & 1)) * 512 + (lane & 7) * 16);
        const uint32_t ln = opq(lane);
        const bool l0 = ln == 0;
        uint32_t la[4];
#pragma unroll
        for (int i = 0; i < 4; i++) la[i] = opq((sb + OFF_RT + (16 * warp + (lane & 15)) * 128 + (((lane >> 4) ^ (lane & 7)) << 4)) ^ (i << 5));
        uint32_t za[8];
#pragma unroll
        for (int i = 0; i < 6; i++) asm volatile("" : "=r"(za[i]));
        auto cvt = [&](uint32_t (&pk)[8], int f) {
            const float(&e)[20] = e2[f & 1];
#pragma unroll
            for (int i = 0; i < 8; i++) asm volatile("cvt.rn.bf16x2.f32 %0, %1, %2;" : "=r"(pk[i]) : "f"(e[2 * i + 1]), "f"(e[2 * i]));
            uint32_t &z0 = za[2 * (f >> 3)], &z1 = za[2 * (f >> 3) + 1];
            asm volatile("{\n.reg .pred p;\nsetp.eq.u32 p, %6, %7;\n@p cvt.rn.bf16x2.f32 %0, %2, %4;\n@p cvt.rn.bf16x2.f32 %1, %3, %5;\n}\n"
                         : "+r"(z0), "+r"(z1)
                         : "f"(e[16]), "f"(e[18]), "f"((f & 1) ? __uint_as_float(z0) : 0.f), "f"((f & 1) ? __uint_as_float(z1) : 0.f), "r"(ln & 3), "r"((f >> 1) & 3));
        };
        auto store = [&](const uint32_t (&pk)[8], int f) {
            stsm_x4_t(sa + sb + OFF_EW + f * EWP, pk[0], pk[1], pk[2], pk[3]);
            stsm_x4_t(sa + sb + OFF_EW + f * EWP + 256, pk[4], pk[5], pk[6], pk[7]);
        };
        auto load1 = [&](auto VC, int i, uint32_t o) {
            constexpr int v = decltype(VC)::value;
            ldsm_x4(la[i ^ (2 * (v & 1))] + o, A[v][i][0], A[v][i][1], A[v][i][2], A[v][i][3]);
        };
        auto mma_e = [&](auto VC) {
            constexpr int v = decltype(VC)::value;
            uint32_t(&ai)[4][4] = A[v];
            wgmma_m64n40k16_rs_tb<2>(e2[v & 1], ai[0], dw);
            wgmma_m64n40k16_rs_tb<1>(e2[v & 1], ai[1], dw + 128);
            wgmma_m64n40k16_rs_tb<1>(e2[v & 1], ai[2], dw + 256);
            wgmma_m64n40k16_rs_tb<1>(e2[v & 1], ai[3], dw + 384);
        };
        auto mma_d1 = [&](auto VC, int i, int sc) {
            constexpr int v = decltype(VC)::value, st = (v + 2) & 3;
            wgmma_m64n128k16_rs_tb(acc, A[v][i], dr + st * (HS_BYTES >> 4) + 128 * i, sc);
        };
        auto mma_d = [&](auto VC, int sc) {
            wgmma_fence();
#pragma unroll
            for (int i = 0; i < 4; i++) mma_d1(VC, i, i ? 1 : sc);
            wgmma_commit();
        };
        auto mma_e1 = [&](auto VC) {
            wgmma_fence();
            mma_e(VC);
            wgmma_commit();
        };
        auto load = [&](auto VC, uint32_t o) {
#pragma unroll
            for (int i = 0; i < 4; i++) load1(VC, i, o);
        };
#define READY(k) asm volatile("bar.sync %0, 160;" ::"n"(4 + ((k) & 3)) : "memory")
        using I0 = std::integral_constant<int, 0>;
        using I1 = std::integral_constant<int, 1>;
        using I2 = std::integral_constant<int, 2>;
        using I3 = std::integral_constant<int, 3>;
        uint32_t pk[8];
        mbar_wait(BAR(B_F), 0);
        TS(19);
        load(I0{}, 0);
        static_for<0, JIT>([&](auto KC) {
            constexpr int k = decltype(KC)::value;
            std::integral_constant<int, k & 3> UC;
            if (k > 1) cvt(pk, k - 2);
            mma_e1(UC);
            mbar_wait(BAR(B_W + k), 0);
            mma_d(UC, k);
            wgmma_wait<2>();
            if (k > 0 && l0) mbar_arrive(BAR(B_EMPTY + k - 1));
            if (k > 1) store(pk, k - 2);
            mbar_wait(BAR(((k & 1) && k < JIT - 1 ? B_F : B_PAIR) + (k + 1) / 2), 0);
            load(std::integral_constant<int, (k + 1) & 3>{}, ((k + 1 + 11 * (~k & 1)) / 2) * RT);
        });
        load(std::integral_constant<int, (JIT + 1) & 3>{}, ((JIT + 12) / 2) * RT);
        mbar_wait(BAR(B_PAIR + JIT / 2 + 1), 0);
        TS(20);
        static_for<JIT, 22>([&](auto KC) {
            constexpr int k = decltype(KC)::value;
            std::integral_constant<int, k & 3> UC;
            cvt(pk, k - 2);
            store(pk, k - 2);
            load(std::integral_constant<int, (k & 3) ^ 2>{}, ((k + 2 + 11 * (k & 1)) / 2) * RT);
            mma_e1(UC);
            READY(k);
            mma_d(UC, 1);
            wgmma_wait<2>();
            if (l0) mbar_arrive(BAR(B_EMPTY + k - 1));
        });
        {
            uint32_t p2[8];
            cvt(pk, 20);
            store(pk, 20);
            load(I0{}, 12 * RT);
            mma_e1(I2{});
            wgmma_wait<2>();
            cvt(pk, 21);
            mma_e1(I3{});
            store(pk, 21);
            READY(22);
            READY(23);
            wgmma_wait<2>();
            if (l0) mbar_arrive(BAR(B_EMPTY + 21));
            load(I1{}, 13 * RT);
            wgmma_wait<1>();
            cvt(pk, 22);
            mma_e1(I0{});
            store(pk, 22);
            wgmma_wait<1>();
            cvt(pk, 23);
            mma_e1(I1{});
            auto mma_h = [&](auto VC, int hh) {
                mma_d1(VC, 2 * hh, 1);
                mma_d1(VC, 2 * hh + 1, 1);
                wgmma_commit();
            };
            mma_h(I2{}, 0);
            store(pk, 23);
            wgmma_wait<1>();
            if (l0) mbar_arrive(BAR(B_ZRDY));
            TS(2);
            za[6] = za[7] = 0u;
            cvt(pk, 24);
            cvt(p2, 25);
#pragma unroll
            for (int i = 0; i < 6; i++) za[i] |= p2[7] & (ln >> 5);
            constexpr uint64_t d1 = make_desc(SB0 + OFF_SEF, 256, 128, 0), d2 = make_desc(SB0 + OFF_SEF + 1024, 512, 128, 0);
            float h[8], o[16];
#pragma unroll
            for (int i = 0; i < 16; i++) asm volatile("" : "=f"(o[i]), "=f"(h[i & 7]));
            wgmma_fence();
            wgmma_m64n16k16_rs<0>(h, za, d1);
            wgmma_m64n16k16_rs<1>(h, za + 4, d1 + 32);
            wgmma_commit();
            mma_h(I2{}, 1);
            mma_d(I3{}, 1);
            wgmma_wait<2>();
            const uint32_t ha0 = pack_bf16(gelu2(h[0]), gelu2(h[1])), ha1 = pack_bf16(gelu2(h[2]), gelu2(h[3])), ha2 = pack_bf16(gelu2(h[4]), gelu2(h[5])),
                           ha3 = pack_bf16(gelu2(h[6]), gelu2(h[7]));
            wgmma_fence();
            wgmma_m64n32k16_rs<2>(o, ha0, ha1, ha2, ha3, d2);
            wgmma_commit();
            wgmma_wait<2>();
            if (l0) mbar_arrive(BAR(B_EMPTY + 22));
            READY(24);
            mma_d(I0{}, 1);
            READY(25);
            store(pk, 24);
            store(p2, 25);
            wgmma_wait<1>();
            if (l0) mbar_arrive(BAR(B_EMPTY + 23));
            mma_d(I1{}, 1);
#pragma unroll
            for (int i = 0; i < 2; i++) {
                uint32_t a[4];
#pragma unroll
                for (int k = 0; k < 4; k++) a[k] = pack_bf16(fmaf(tanh_fast(o[8 * i + 2 * k]), 0.5f, 0.5f), fmaf(tanh_fast(o[8 * i + 2 * k + 1]), 0.5f, 0.5f));
                sts128(sb + OFF_AP + i * 2048 + warp * 512 + ln * 16, a[0], a[1], a[2], a[3]);
            }
            __syncwarp();
            if (l0) mbar_arrive(BAR(B_EWRDY));
            wgmma_wait<1>();
            if (l0) mbar_arrive(BAR(B_EMPTY + 24));
            TS(3);
        }
        {
            wgmma_wait<0>();
            if (l0) mbar_arrive(BAR(B_EMPTY + 25));
            uint32_t hw[32];
#pragma unroll
            for (int i = 0; i < 32; i++) asm volatile("cvt.rn.bf16x2.f32 %0, %1, %2;" : "=r"(hw[i]) : "f"(acc[2 * i + 1]), "f"(acc[2 * i]));
            asm volatile("setmaxnreg.dec.sync.aligned.u32 %0;" ::"n"(R_DEEP2));
            TS(4);
            float o[4] = {0.f, 0.f, 0.f, 0.f};
            int l2;
            asm volatile("mov.u32 %0, %%laneid;" : "=r"(l2));
#pragma unroll
            for (int it = 0; it < 8; it++) {
                uint32_t b0, b1;
                asm volatile("ld.shared.v2.u32 {%0,%1}, [%2];" : "=r"(b0), "=r"(b1) : "r"(sb + OFF_W2 + 8 * (l2 & 3) + it * 32));
                mma16816(o, gelu2p(hw[4 * it]), gelu2p(hw[4 * it + 1]), gelu2p(hw[4 * it + 2]), gelu2p(hw[4 * it + 3]), b0, b1);
            }
            send_partial(sb, rank * 3, warp, l2 >> 2, l2 & 3, 0.5f * o[0], 0.5f * o[2]);
        }
        TS(5);
    } else {
        const int wgc = (warp >> 2) - 1, w4 = warp & 3;
        const char* so = (const char*)table + 16 * (lane & 7);
        auto rp = [&](uint32_t i) { return row_ptr(so, i); };
        const uint32_t d0 = opq(sb + OFF_RT + b * 128 + (((lane ^ b) & 7) << 4)), d1 = opq((d0 ^ 64) + 6 * RT);
        uint32_t c0;
        auto until = [&](int f) {
            for (;;) {
                uint32_t c;
                asm volatile("mov.u32 %0, %%clock;" : "=r"(c)::"memory");
                if (c - c0 >= f * 300) break;
                __nanosleep(32);
            }
        };
        {
            const int ia[4] = {i0a.x, i0a.y, i1a.x, i1a.y}, ib[4] = {i0b.x, i0b.y, i1b.x, i1b.y};
            static_for<0, NFIRST>([&](auto FC) {
                constexpr int f = decltype(FC)::value, o = (f >> 1) * RT;
                if (f) until(f);
                cp_async16(((f & 1) ? d1 : d0) + o, rp(ia[f]));
                cp_async16(((f & 1) ? d1 : d0) + o + 4096, rp(ib[f]));
                cp_async_mbar_arrive_noinc(BAR(((f & 1) ? B_PAIR : B_F) + (f >> 1)));
                if (f == 0) asm volatile("mov.u32 %0, %%clock;" : "=r"(c0)::"memory");
            });
            if (wgc == 0) TS(6);
        }
        asm volatile("setmaxnreg.inc.sync.aligned.u32 %0;" ::"n"(R_CR1));
        uint32_t M[8][12], y[4][2];
        {
            const uint32_t pa = opq(sb + OFF_RT + (t & 1) * 6 * RT + (16 * w4 + g) * 128 + (((4 * rank + 2 * wgc) ^ g ^ (4 * (t & 1))) << 4)), t1 = opq(t >> 1);
            const uint32_t ia = opq(sb + OFF_IDX + b * NF * 4);
#pragma unroll
            for (int i = 0; i < 96; i++) asm volatile("" : "=r"(M[i / 12][i % 12]));
            mbar_wait(BAR(B_IDX), 0);
            uint32_t x[13][4];
#pragma unroll
            for (int p = 2; p < 13; p++)
                asm volatile("ld.shared.v2.u32 {%0,%1}, [%4];\nld.shared.v2.u32 {%2,%3}, [%4 + 3328];" : "=r"(x[p][0]), "=r"(x[p][2]), "=r"(x[p][1]), "=r"(x[p][3]) : "r"(ia + p * 8));
            const uint32_t pb = opq(pa ^ 16);
            auto conv = [&](int G) {
#pragma unroll
                for (int i = 0; i < 16; i++) {
                    uint32_t &u = M[i >> 1][4 * G + 2 * (i & 1)], &v = M[i >> 1][4 * G + 2 * (i & 1) + 1];
                    asm volatile("{\n.reg .b32 t;\nprmt.b32 t, %0, %1, 0x5410;\nprmt.b32 %1, %0, %1, 0x7632;\nmov.b32 %0, t;\n}\n" : "+r"(u), "+r"(v));
                }
#pragma unroll
                for (int i = 0; i < 8; i++)
                    asm volatile("{\n.reg .pred p;\nsetp.eq.u32 p, %5, 2;\n@p st.shared.v4.u32 [%4], {%0,%1,%2,%3};\n}\n" ::"r"(M[i & 4][4 * G + (i & 3)]), "r"(M[(i & 4) + 1][4 * G + (i & 3)]),
                                 "r"(M[(i & 4) + 2][4 * G + (i & 3)]), "r"(M[(i & 4) + 3][4 * G + (i & 3)]), "r"(pa), "r"(t1));
            };
            auto gather = [&](auto PC) {
                constexpr int p = decltype(PC)::value;
                constexpr uint32_t o1 = (p < 12 ? p : 7) * RT;
                if (p < 6) until(2 * p);
                cp_async16(d0 + p * RT, rp(x[p][0]));
                cp_async16(d0 + p * RT + 4096, rp(x[p][1]));
                if (p < 6) until(2 * p + 1);
                cp_async16(d1 + o1, rp(x[p][2]));
                cp_async16(d1 + o1 + 4096, rp(x[p][3]));
                cp_async_mbar_arrive_noinc(BAR(B_PAIR + p));
            };
            auto pick = [&](auto QC) {
                constexpr int q = decltype(QC)::value, c = 4 * (q >> 2) + ((q >> 1) & 1);
#pragma unroll
                for (int i = 0; i < 4; i++)
                    asm volatile("{\n.reg .pred p;\nsetp.eq.u32 p, %5, %6;\n@p ld.shared.v4.u32 {%0,%1,%2,%3}, [%4];\n}\n"
                                 : "+r"(M[2 * (i & 2)][c + 2 * (i & 1)]), "+r"(M[2 * (i & 2) + 1][c + 2 * (i & 1)]), "+r"(M[2 * (i & 2) + 2][c + 2 * (i & 1)]),
                                   "+r"(M[2 * (i & 2) + 3][c + 2 * (i & 1)])
                                 : "r"(((i & 2) ? pb : pa) + q * RT + (i & 1) * 1024), "r"(t1), "n"(q & 1));
                __syncwarp();
                if (elect_one()) mbar_arrive(BAR(B_W + 2 * q + 1 + (q == 0)));
                if (q == 4 || q == 8) conv(q / 4 - 1);
            };
#define IC(x) std::integral_constant<int, x>{}
            gather(IC(2));
            gather(IC(3));
            static_for<0, 3>([&](auto QC) {
                constexpr int q = decltype(QC)::value;
                mbar_wait(BAR(B_PAIR + q), 0);
                pick(QC);
                if constexpr (q < 2) gather(IC(q + 4));
            });
            static_for<3, 12>([&](auto QC) {
                constexpr int q = decltype(QC)::value, p = q < 9 ? q + 3 : q == 10 ? 12 : 0;
                mbar_wait(BAR(B_EMPTY + 2 * q - 6 + (q == 3)), 0);
                mbar_wait(BAR(B_PAIR + q), 0);
                if constexpr (p) gather(IC(p));
                pick(QC);
            });
            const uint32_t ta = sb + OFF_RT + 12 * RT + (16 * w4 + g) * 128 + (((4 * rank + 2 * wgc + (t >> 1)) ^ g) << 4) + 8 * (t & 1);
            mbar_wait(BAR(B_PAIR + 12), 0);
#pragma unroll
            for (int k = 0; k < 4; k++) asm volatile("ld.shared.v2.u32 {%0,%1}, [%2];" : "=r"(y[k][0]), "=r"(y[k][1]) : "r"(((k & 1) ? (ta ^ 64) + RT : ta) + (k >> 1) * 1024));
            __syncwarp();
            if (elect_one()) mbar_arrive(BAR(B_W + 25));
            conv(2);
        }
        uint32_t TL[4][2];
        uint32_t ap[8], a0, a1;
        uint32_t A0[8], A1[8], Aq[8], w[8], aq;
        {
            const int r = lane & 7, bh = (lane >> 3) & 1, ig = lane >> 4;
            const uint32_t x = sb + OFF_EW + wgc * 256 + (2 * w4 + bh) * 512 + (8 * ig + 4 * (r & 1) + (r >> 1)) * EWP;
            a0 = opq(x);
            a1 = opq(x + (!ig || r == 0 ? 16 : r == 1 ? 13 : 8) * EWP);
            aq = opq(sb + OFF_AP + w4 * 512 + lane * 16);
        }
        mbar_wait(BAR(B_CFULL), 0);
        mbar_wait(BAR(B_EWRDY), 0);
        u_lda(A0, a0, a1);
#pragma unroll
        for (int i = 0; i < 2; i++) {
            const uint4 v = lds128(aq + i * 2048);
            ap[4 * i] = v.x, ap[4 * i + 1] = v.y, ap[4 * i + 2] = v.z, ap[4 * i + 3] = v.w;
        }
        if (wgc == 0) TS(60);
        asm volatile("setmaxnreg.inc.sync.aligned.u32 %0;" ::"n"(R_CR2));
        if (wgc == 0) TS(61);
        asm volatile("mov.u32 %0, %%clock;\nand.b32 %0, %0, %1;" : "=r"(aq) : "r"(warp >> 4));
        a0 |= aq, a1 |= aq;
#pragma unroll
        for (int k = 0; k < 8; k++) {
            TL[k >> 1][k & 1] = __byte_perm(y[2 * (k & 1)][k >> 2], y[2 * (k & 1) + 1][k >> 2], (0x5410 + 0x2222 * ((k >> 1) & 1)) | aq);
            ap[k] |= aq, A0[k] |= aq & TL[k >> 1][k & 1];
        }
        constexpr uint64_t dt = make_desc(SB0 + OFF_TW, 512, 128, 0), dqc = make_desc(SB0 + OFF_ID, 128, 128, 0);
        const uint64_t dq = uni64(dqc + (sb >> 28));
        const uint64_t desc = dt + wgc * (CHUNK >> 4);
        auto dsc = [&](int e, int pq) { return desc + ((CPOS >> (4 * (e >> 1))) & 7) * (2 * CHUNK >> 4) + ((e & 1) * 2 + pq) * (TILE >> 4); };
        float S[4], accP[16], accQ[16];
#pragma unroll
        for (int i = 0; i < 16; i++) asm volatile("" : "=f"(accP[i]), "=f"(accQ[i]));
        u_lda(A1, a0 + 16, a1 + 16);
#pragma unroll
        for (int i = 0; i < 4; i++) asm volatile("" : "=f"(S[i]));
#pragma unroll
        for (int k = 0; k < 8; k++) Aq[k] = hmul2_bf16(A0[k], ap[k]);
        wgmma_fence();
        u_mma(accP, A0, dsc(0, 0));
        wgmma_commit();
        u_mma(accQ, Aq, dsc(0, 1));
        wgmma_commit();
        if (wgc == 0) TS(62);
        auto pack8 = [&](uint32_t (&d)[8], const float (&a)[16]) {
#pragma unroll
            for (int k = 0; k < 8; k++) asm volatile("cvt.rn.bf16x2.f32 %0, %1, %2;" : "=r"(d[k]) : "f"(a[2 * k + 1]), "f"(a[2 * k]));
        };
        static_for<0, 8>([&](auto PC) {
            constexpr int p = decltype(PC)::value, e = 2 * p;
            auto mw = [&](int s, int k) { return k < 6 ? M[p][2 * k + s] : TL[(e + s) & 3][k - 6]; };
            uint32_t tp[8], tq[8];
            wgmma_wait<1>();
            pack8(tp, accP);
            wgmma_fence();
            u_mma(accP, A1, dsc(e + 1, 0));
            if (p) {
                wgmma_m64n8k16_rs(S, w, dq, p > 1);
                wgmma_m64n8k16_rs(S, w + 4, dq, 1);
            }
            wgmma_commit();
            if (p < 7) u_lda(A0, a0 + 16 * e + 32, a1 + 16 * e + 32);
            wgmma_wait<1>();
            pack8(tq, accQ);
#pragma unroll
            for (int k = 0; k < 8; k++) Aq[k] = hmul2_bf16(A1[k], ap[k]);
            wgmma_fence();
            u_mma(accQ, Aq, dsc(e + 1, 1));
            wgmma_commit();
#pragma unroll
            for (int k = 0; k < 8; k++) tq[k] = hfma2_bf16(tq[k], ap[k], tp[k]);
            if (p == 0 || p == 2 || p == 5) mbar_wait(BAR(B_CFULL + 1 + p / 2), 0);
            wgmma_wait<1>();
            pack8(tp, accP);
            if (p < 7) {
                wgmma_fence();
                u_mma(accP, A0, dsc(e + 2, 0));
                wgmma_commit();
                u_lda(A1, a0 + 16 * e + 48, a1 + 16 * e + 48);
            }
#pragma unroll
            for (int k = 0; k < 8; k++) w[k] = hmul2_bf16(tq[k], mw(0, k));
            wgmma_wait<(p < 7)>();
            if (p == 0 && elect_one()) mbar_arrive(BAR(B_CDONE));
            pack8(tq, accQ);
            if (p < 7) {
#pragma unroll
                for (int k = 0; k < 8; k++) Aq[k] = hmul2_bf16(A0[k], ap[k]);
                wgmma_fence();
                u_mma(accQ, Aq, dsc(e + 2, 1));
                wgmma_commit();
            }
#pragma unroll
            for (int k = 0; k < 8; k++) w[k] = hfma2_bf16(hfma2_bf16(tq[k], ap[k], tp[k]), mw(1, k), w[k]);
        });
        int tid2;
        asm volatile("mov.u32 %0, %%laneid;" : "=r"(tid2));
        wgmma_fence();
        wgmma_m64n8k16_rs(S, w, dq, 1);
        wgmma_m64n8k16_rs(S, w + 4, dq, 1);
        wgmma_commit();
        wgmma_wait<0>();
        send_partial(sb, rank * 3 + 1 + wgc, w4, tid2 >> 2, tid2 & 3, S[0], S[2]);
        if (wgc == 0) TS(14);
    }
#undef BAR
}

typedef CUresult (*PFN_encodeTiled)(CUtensorMap*, CUtensorMapDataType, cuuint32_t, void*, const cuuint64_t*, const cuuint64_t*,
                                    const cuuint32_t*, const cuuint32_t*, CUtensorMapInterleave, CUtensorMapSwizzle,
                                    CUtensorMapL2promotion, CUtensorMapFloatOOBfill);

}

extern "C" void kernel_launch(void* const* d_in, const int* in_sizes, int n_in, void* d_out, int out_size) {
    const int* idx = (const int*)d_in[0];
    const __nv_bfloat16* table = (const __nv_bfloat16*)d_in[1];
    const __nv_bfloat16* se_w1 = (const __nv_bfloat16*)d_in[2];
    const __nv_bfloat16* se_w2 = (const __nv_bfloat16*)d_in[3];
    const __nv_bfloat16* w_bi = (const __nv_bfloat16*)d_in[4];
    const __nv_bfloat16* w_cross = (const __nv_bfloat16*)d_in[5];
    const __nv_bfloat16* w_deep1 = (const __nv_bfloat16*)d_in[6];
    const __nv_bfloat16* w_deep2 = (const __nv_bfloat16*)d_in[7];
    __nv_bfloat16* out = (__nv_bfloat16*)d_out;

    static PFN_encodeTiled enc = nullptr;
    if (!enc) {
        void* fn = nullptr;
        cudaDriverEntryPointQueryResult qres;
        cudaGetDriverEntryPoint("cuTensorMapEncodeTiled", &fn, cudaEnableDefault, &qres);
        enc = (PFN_encodeTiled)fn;
        cudaFuncSetAttribute(fused_kernel, cudaFuncAttributeMaxDynamicSharedMemorySize, SMEM);
    }
    CUtensorMap tm;
    {
        cuuint64_t gdim[3] = {64, (cuuint64_t)(NF * ND), 4};
        cuuint64_t gstr[2] = {(cuuint64_t)NH * 2, 128};
        cuuint32_t box[3] = {64, 64, 2};
        cuuint32_t estr[3] = {1, 1, 1};
        enc(&tm, CU_TENSOR_MAP_DATA_TYPE_BFLOAT16, 3, (void*)w_deep1, gdim, gstr, box, estr, CU_TENSOR_MAP_INTERLEAVE_NONE,
            CU_TENSOR_MAP_SWIZZLE_128B, CU_TENSOR_MAP_L2_PROMOTION_L2_256B, CU_TENSOR_MAP_FLOAT_OOB_FILL_NONE);
    }
    fused_kernel<<<128, 512, SMEM>>>(idx, table, w_deep1, w_bi, w_deep2, w_cross, se_w1, se_w2, out, tm);
}
```

```cpp
#include <cuda_runtime.h>
#include <cuda_bf16.h>
#include <cuda.h>
#include <stdint.h>
#include <type_traits>
#include <utility>

#define R_DEEP 216
#define R_CR1 136
#define R_CR2 216
#define R_DEEP2 56
#define R_PROD 24

namespace {

constexpr int NF = 26, ND = 64, NH = 256, NFR = 13;

#define TS(slot)
#define TSL(slot)

__device__ __forceinline__ uint32_t smem_u32(const void* p) { return (uint32_t)__cvta_generic_to_shared(p); }
__device__ __forceinline__ void mbar_init(uint32_t bar, uint32_t cnt) {
    asm volatile("mbarrier.init.shared::cta.b64 [%0], %1;" ::"r"(bar), "r"(cnt));
}
__device__ __forceinline__ void mbar_expect_tx(uint32_t bar, uint32_t bytes) {
    asm volatile("mbarrier.arrive.expect_tx.shared::cta.b64 _, [%0], %1;" ::"r"(bar), "r"(bytes) : "memory");
}
__device__ __forceinline__ void mbar_arrive(uint32_t bar) {
    asm volatile("mbarrier.arrive.shared::cta.b64 _, [%0];" ::"r"(bar) : "memory");
}
__device__ __forceinline__ void mbar_wait(uint32_t bar, uint32_t parity) {
    asm volatile(
        "{\n"
        ".reg .pred p;\n"
        "WAIT_%=:\n"
        "mbarrier.try_wait.parity.shared::cta.b64 p, [%0], %1;\n"
        "@p bra.uni DONE_%=;\nbra.uni WAIT_%=;\nDONE_%=:\n"
        "}\n" ::"r"(bar),
        "r"(parity)
        : "memory");
}
__device__ __forceinline__ uint32_t opq(uint32_t x) { return __shfl_xor_sync(0xffffffffu, x, 0); }
__device__ __forceinline__ uint64_t uni64(uint64_t x) {
    uint32_t lo = (uint32_t)x, hi = (uint32_t)(x >> 32);
    asm volatile("shfl.sync.idx.b32 %0, %0, 0, 31, -1;\nshfl.sync.idx.b32 %1, %1, 0, 31, -1;" : "+r"(lo), "+r"(hi));
    return ((uint64_t)hi << 32) | lo;
}
__device__ __forceinline__ bool elect_one() {
    uint32_t r;
    asm volatile("{\n.reg .pred p;\nelect.sync _|p, 0xffffffff;\nselp.u32 %0, 1, 0, p;\n}\n" : "=r"(r));
    return r;
}
__device__ __forceinline__ const void* row_ptr(const void* base, uint32_t i) {
    const void* r;
    asm("mad.wide.u32 %0, %1, 128, %2;" : "=l"(r) : "r"(i), "l"(base));
    return r;
}
__device__ __forceinline__ void mbar_wait_bounded(uint32_t bar, uint32_t parity) {
    asm volatile(
        "{\n"
        ".reg .pred p;\n"
        ".reg .u32 c;\n"
        "mov.u32 c, 0;\n"
        "WAIT_%=:\n"
        "mbarrier.try_wait.parity.shared::cta.b64 p, [%0], %1;\n"
        "@p bra.uni DONE_%=;\n"
        "add.u32 c, c, 1;\n"
        "setp.lt.u32 p, c, 0x400000;\n"
        "@p bra.uni WAIT_%=;\n"
        "trap;\n"
        "DONE_%=:\n"
        "}\n" ::"r"(bar),
        "r"(parity)
        : "memory");
}
__device__ __forceinline__ void cp_async16(uint32_t dst, const void* src) {
    asm volatile("cp.async.cg.shared.global [%0], [%1], 16;" ::"r"(dst), "l"(src) : "memory");
}
__device__ __forceinline__ void cp_async_mbar_arrive_noinc(uint32_t bar) {
    asm volatile("cp.async.mbarrier.arrive.noinc.shared::cta.b64 [%0];" ::"r"(bar) : "memory");
}
__device__ __forceinline__ void tma_load_3d(uint32_t dst, const void* tmap, int c0, int c1, int c2, uint32_t bar) {
    asm volatile(
        "cp.async.bulk.tensor.3d.shared::cluster.global.mbarrier::complete_tx::bytes [%0], [%1, {%3, %4, %5}], [%2];" ::"r"(dst),
        "l"(tmap), "r"(bar), "r"(c0), "r"(c1), "r"(c2)
        : "memory");
}
__device__ __forceinline__ void bulk_load(uint32_t dst, const void* src, uint32_t bytes, uint32_t bar) {
    asm volatile("cp.async.bulk.shared::cluster.global.mbarrier::complete_tx::bytes [%0], [%1], %2, [%3];" ::"r"(dst), "l"(src), "r"(bytes),
                 "r"(bar)
                 : "memory");
}
__device__ __forceinline__ void fence_proxy_async() { asm volatile("fence.proxy.async.shared::cta;" ::: "memory"); }
__device__ __forceinline__ void wgmma_fence() { asm volatile("wgmma.fence.sync.aligned;" ::: "memory"); }
__device__ __forceinline__ void wgmma_commit() { asm volatile("wgmma.commit_group.sync.aligned;" ::: "memory"); }
template <int N> __device__ __forceinline__ void wgmma_wait() { asm volatile("wgmma.wait_group.sync.aligned %0;" ::"n"(N) : "memory"); }

__device__ __forceinline__ void ldsm_x4(uint32_t addr, uint32_t& r0, uint32_t& r1, uint32_t& r2, uint32_t& r3) {
    asm volatile("ldmatrix.sync.aligned.m8n8.x4.shared.b16 {%0,%1,%2,%3}, [%4];" : "=r"(r0), "=r"(r1), "=r"(r2), "=r"(r3) : "r"(addr));
}
__device__ __forceinline__ void ldsm_x4_t(uint32_t addr, uint32_t& r0, uint32_t& r1, uint32_t& r2, uint32_t& r3) {
    asm volatile("ldmatrix.sync.aligned.m8n8.x4.trans.shared.b16 {%0,%1,%2,%3}, [%4];" : "=r"(r0), "=r"(r1), "=r"(r2), "=r"(r3) : "r"(addr));
}
__device__ __forceinline__ void stsm_x4_t(uint32_t addr, uint32_t r0, uint32_t r1, uint32_t r2, uint32_t r3) {
    asm volatile("stmatrix.sync.aligned.m8n8.x4.trans.shared.b16 [%0], {%1,%2,%3,%4};" ::"r"(addr), "r"(r0), "r"(r1), "r"(r2), "r"(r3) : "memory");
}
__device__ __forceinline__ uint4 lds128(uint32_t addr) {
    uint4 v;
    asm volatile("ld.shared.v4.u32 {%0,%1,%2,%3}, [%4];" : "=r"(v.x), "=r"(v.y), "=r"(v.z), "=r"(v.w) : "r"(addr));
    return v;
}
__device__ __forceinline__ uint32_t lds32(uint32_t addr) {
    uint32_t v;
    asm volatile("ld.shared.u32 %0, [%1];" : "=r"(v) : "r"(addr));
    return v;
}
__device__ __forceinline__ void sts128(uint32_t addr, uint32_t a, uint32_t b, uint32_t c, uint32_t d) {
    asm volatile("st.shared.v4.u32 [%0], {%1,%2,%3,%4};" ::"r"(addr), "r"(a), "r"(b), "r"(c), "r"(d) : "memory");
}
__device__ __forceinline__ void mma16816(float (&c)[4], uint32_t a0, uint32_t a1, uint32_t a2, uint32_t a3, uint32_t b0, uint32_t b1) {
    asm("mma.sync.aligned.m16n8k16.row.col.f32.bf16.bf16.f32 {%0,%1,%2,%3}, {%4,%5,%6,%7}, {%8,%9}, {%0,%1,%2,%3};"
        : "+f"(c[0]), "+f"(c[1]), "+f"(c[2]), "+f"(c[3])
        : "r"(a0), "r"(a1), "r"(a2), "r"(a3), "r"(b0), "r"(b1));
}
__device__ __forceinline__ uint32_t pack_bf16(float lo, float hi) {
    uint32_t r;
    asm("cvt.rn.bf16x2.f32 %0, %1, %2;" : "=r"(r) : "f"(hi), "f"(lo));
    return r;
}
__device__ __forceinline__ uint32_t hmul2_bf16(uint32_t a, uint32_t b) {
    uint32_t r;
    asm("mul.rn.bf16x2 %0, %1, %2;" : "=r"(r) : "r"(a), "r"(b));
    return r;
}
__device__ __forceinline__ float tanh_fast(float x) {
    float r;
    asm("tanh.approx.f32 %0, %1;" : "=f"(r) : "f"(x));
    return r;
}
#define WG_ACC8(c, b) c(acc[b]), c(acc[b + 1]), c(acc[b + 2]), c(acc[b + 3]), c(acc[b + 4]), c(acc[b + 5]), c(acc[b + 6]), c(acc[b + 7])
#define WG_N128(c, sc)                                                                                                              \
    asm volatile(                                                                                                                   \
        "{\n"                                                                                                                       \
        ".reg .pred p;\n"                                                              \
        "setp.ne.b32 p, " sc ", 0;\n"                                                                                               \
        "wgmma.mma_async.sync.aligned.m64n128k16.f32.bf16.bf16 "                                                                    \
        "{%0,%1,%2,%3,%4,%5,%6,%7,%8,%9,%10,%11,%12,%13,%14,%15,"                                                                   \
        "%16,%17,%18,%19,%20,%21,%22,%23,%24,%25,%26,%27,%28,%29,%30,%31,"                                                          \
        "%32,%33,%34,%35,%36,%37,%38,%39,%40,%41,%42,%43,%44,%45,%46,%47,"                                                          \
        "%48,%49,%50,%51,%52,%53,%54,%55,%56,%57,%58,%59,%60,%61,%62,%63},"                                                         \
        " {%64,%65,%66,%67}, %68, p, 1, 1, 1;\n"                                                                                    \
        "}\n"                                                                                                                       \
        : WG_ACC8(c, 0), WG_ACC8(c, 8), WG_ACC8(c, 16), WG_ACC8(c, 24), WG_ACC8(c, 32), WG_ACC8(c, 40), WG_ACC8(c, 48), WG_ACC8(c, 56) \
        : "r"(a[0]), "r"(a[1]), "r"(a[2]), "r"(a[3]), "l"(db), "r"(scv))
__device__ __forceinline__ void wgmma_m64n128k16_rs_tb(float (&acc)[64], const uint32_t (&a)[4], uint64_t db, int scv) {
    WG_N128("+f", "%69");
}
#define WG_N40(c, sc)                                                                         \
    asm volatile(                                                                             \
        "{\n"                                                                                 \
        ".reg .pred p;\n"                        \
        "setp.ne.b32 p, " sc ", 0;\n"                                                         \
        "wgmma.mma_async.sync.aligned.m64n40k16.f32.bf16.bf16 "                               \
        "{%0,%1,%2,%3,%4,%5,%6,%7,%8,%9,%10,%11,%12,%13,%14,%15,%16,%17,%18,%19},"            \
        " {%20,%21,%22,%23}, %24, p, 1, 1, 1;\n"                                              \
        "}\n"                                                                                 \
        : WG_ACC8(c, 0), WG_ACC8(c, 8), c(acc[16]), c(acc[17]), c(acc[18]), c(acc[19])        \
        : "r"(a[0]), "r"(a[1]), "r"(a[2]), "r"(a[3]), "l"(db))
template <int SC>
__device__ __forceinline__ void wgmma_m64n40k16_rs_tb(float (&acc)[20], const uint32_t (&a)[4], uint64_t db) {
    if constexpr (SC == 1) WG_N40("+f", "1");
    else if constexpr (SC == 2) WG_N40("+f", "0");
    else WG_N40("=f", "0");
}
#define WG_N32(c, sc)                                                   \
    asm volatile(                                                       \
        "{\n"                                                           \
        ".reg .pred p;\n"           \
        "setp.ne.b32 p, " sc ", 0;\n"                                   \
        "wgmma.mma_async.sync.aligned.m64n32k16.f32.bf16.bf16 "         \
        "{%0,%1,%2,%3,%4,%5,%6,%7,%8,%9,%10,%11,%12,%13,%14,%15},"      \
        " {%16,%17,%18,%19}, %20, p, 1, 1, 0;\n"                        \
        "}\n"                                                           \
        : WG_ACC8(c, 0), WG_ACC8(c, 8)                                  \
        : "r"(a0), "r"(a1), "r"(a2), "r"(a3), "l"(db))
template <int SC>
__device__ __forceinline__ void wgmma_m64n32k16_rs(float (&acc)[16], uint32_t a0, uint32_t a1, uint32_t a2, uint32_t a3, uint64_t db) {
    if constexpr (SC == 1) WG_N32("+f", "1");
    else if constexpr (SC == 2) WG_N32("+f", "0");
    else WG_N32("=f", "0");
}

__host__ __device__ constexpr uint64_t make_desc(uint32_t addr, uint32_t lbo_bytes, uint32_t sbo_bytes, uint32_t swz) {
    uint64_t d = 0;
    d |= (uint64_t)((addr & 0x3FFFF) >> 4);
    d |= (uint64_t)((lbo_bytes >> 4) & 0x3FFF) << 16;
    d |= (uint64_t)((sbo_bytes >> 4) & 0x3FFF) << 32;
    d |= (uint64_t)swz << 62;
    return d;
}
__device__ __forceinline__ uint32_t ldg_u16(const __nv_bfloat16* p) { return (uint32_t)__ldg(reinterpret_cast<const unsigned short*>(p)); }
template <int N, class F, int... I>
__device__ __forceinline__ void static_for_impl(F&& f, std::integer_sequence<int, I...>) {
    (f(std::integral_constant<int, N + I>{}), ...);
}
template <int B, int E, class F>
__device__ __forceinline__ void static_for(F&& f) {
    static_for_impl<B>(f, std::make_integer_sequence<int, E - B>{});
}

__device__ __forceinline__ uint32_t hfma2_bf16(uint32_t a, uint32_t b, uint32_t c) {
    uint32_t r;
    asm("fma.rn.bf16x2 %0, %1, %2, %3;" : "=r"(r) : "r"(a), "r"(b), "r"(c));
    return r;
}
__device__ __forceinline__ float gelu2(float x) {
    const float k0 = 0.7978845608028654f, k01 = 0.7978845608028654f * 0.044715f;
    return fmaf(x, tanh_fast(x * fmaf(x * x, k01, k0)), x);
}
__device__ __forceinline__ uint32_t gelu2p(uint32_t x) {
    uint32_t t;
    const uint32_t u = hmul2_bf16(x, hfma2_bf16(hmul2_bf16(x, x), 0x3D123D12u, 0x3F4C3F4Cu));
    asm("tanh.approx.bf16x2 %0, %1;" : "=r"(t) : "r"(u));
    return hfma2_bf16(x, t, x);
}
__device__ __forceinline__ void wgmma_m64n8k16_rs(float (&acc)[4], const uint32_t* a, uint64_t db, int sc) {
    asm volatile("{\n.reg .pred p;\nsetp.ne.b32 p, %9, 0;\nwgmma.mma_async.sync.aligned.m64n8k16.f32.bf16.bf16 {%0,%1,%2,%3}, {%4,%5,%6,%7}, %8, p, 1, 1, 0;\n}\n"
                 : "+f"(acc[0]), "+f"(acc[1]), "+f"(acc[2]), "+f"(acc[3])
                 : "r"(a[0]), "r"(a[1]), "r"(a[2]), "r"(a[3]), "l"(db), "r"(sc));
}

template <int SC>
__device__ __forceinline__ void wgmma_m64n16k16_rs(float (&acc)[8], const uint32_t* a, uint64_t db) {
    asm volatile("{\n.reg .pred p;\nsetp.ne.b32 p, %13, 0;\nwgmma.mma_async.sync.aligned.m64n16k16.f32.bf16.bf16 {%0,%1,%2,%3,%4,%5,%6,%7}, {%8,%9,%10,%11}, %12, p, 1, 1, 0;\n}\n"
                 : WG_ACC8("+f", 0)
                 : "r"(a[0]), "r"(a[1]), "r"(a[2]), "r"(a[3]), "l"(db), "n"(SC));
}

constexpr int SB0 = 1024;
constexpr int SLOT = 4096;
constexpr int EWP = SLOT + 16;
constexpr int OFF_EW = 608;
constexpr int OFF_RT = 1024;
constexpr int RT = 8192;
constexpr int OFF_TW = OFF_RT + 13 * RT;
constexpr int HS_BYTES = 16384;
constexpr int OFF_RING = OFF_RT + 19 * RT;
constexpr int OFF_WBI = OFF_RT + 18 * RT;
constexpr int OFF_IDX = OFF_RT + 17 * RT;
constexpr int OFF_SEF = OFF_RING + 4 * HS_BYTES;
constexpr int OFF_AP = OFF_SEF + 2048;
constexpr int OFF_W2 = 0;
constexpr int OFF_DP = OFF_AP + 4096;
constexpr int OFF_ID = OFF_DP + 6 * 32 * 4;
constexpr int OFF_BAR = OFF_ID + 256;
constexpr int TILE = 2048;
constexpr int CHUNK = 4 * TILE;
constexpr int NCHUNK = 16;
constexpr int CPOS = 0x16504321;
static_assert(OFF_TW + 14 * CHUNK == OFF_SEF && OFF_EW + 25 * EWP + SLOT <= OFF_TW, "layout");
static_assert(OFF_RING % 1024 == 0 && OFF_WBI % 1024 == 0 && OFF_ID % 128 == 0, "align");
constexpr int B_CFULL = 0,
              B_F = 4,
              B_W = 16,
              B_EMPTY = 48, B_ZRDY = B_EMPTY + NF, B_CDONE = B_ZRDY + 1,
              B_EWRDY = B_CDONE + 2, B_PAIR = 80,
              B_IDX = B_PAIR + 13, B_FIN = B_PAIR + 14;
constexpr int OFF_TS = OFF_BAR + 768;
constexpr int SMEM = OFF_TS + 512;
static_assert(SMEM <= 232448, "smem");
constexpr int NFIRST = 4;
constexpr int JIT = 4;
constexpr int NUNIT = 128;

__device__ __align__(1024) uint8_t g_wt[2 * NCHUNK * CHUNK];
__device__ unsigned int g_cnt;

__device__ __forceinline__ void u_lda(uint32_t (&A)[8], uint32_t a0, uint32_t a1) {
    ldsm_x4_t(a0, A[0], A[1], A[2], A[3]);
    ldsm_x4_t(a1, A[4], A[5], A[6], A[7]);
}
__device__ __forceinline__ void u_mma(float (&acc)[16], const uint32_t (&A)[8], uint64_t desc) {
    wgmma_m64n32k16_rs<2>(acc, A[0], A[1], A[2], A[3], desc);
    wgmma_m64n32k16_rs<1>(acc, A[4], A[5], A[6], A[7], desc + 64);
}
__device__ __forceinline__ void send_addr(uint32_t sb, int src, int w4, uint32_t& da, uint32_t& db, uint32_t& t) {
    uint32_t rb, l;
    asm volatile("mov.u32 %0, %%laneid;" : "=r"(l));
    asm volatile("mapa.shared::cluster.u32 %0, %1, %2;" : "=r"(rb) : "r"(sb), "r"(w4 >> 1));
    da = opq(rb + OFF_DP + (src * 32 + (w4 & 1) * 16 + 8 * (l & 1) + (l >> 2)) * 4);
    db = opq(rb + OFF_BAR + B_FIN * 8 + (l >> 5));
    t = l & 3;
}
__device__ __forceinline__ void send_partial(uint32_t da, uint32_t db, uint32_t t, float v0, float v1) {
    asm volatile("{\n.reg .pred p;\nsetp.lt.u32 p, %3, 2;\n@p st.async.weak.shared::cluster.mbarrier::complete_tx::bytes.f32 [%0], %1, [%2];\n}\n" ::"r"(da), "f"(t ? v1 : v0),
                 "r"(db), "r"(t)
                 : "memory");
}

__global__ void __cluster_dims__(2, 1, 1) __launch_bounds__(512, 1)
fused_kernel(const int* __restrict__ idx, const __nv_bfloat16* __restrict__ table, const __nv_bfloat16* __restrict__ w1, const __nv_bfloat16* __restrict__ w_bi,
             const __nv_bfloat16* __restrict__ w2, const __nv_bfloat16* __restrict__ w_cross, const __nv_bfloat16* __restrict__ se_w1,
             const __nv_bfloat16* __restrict__ se_w2, __nv_bfloat16* __restrict__ out, const __grid_constant__ CUtensorMap tmW1) {
    extern __shared__ __align__(1024) uint8_t smem_raw[];
    const int tid = threadIdx.x, b = (tid >> 3) & 31;
    const int pb0 = (blockIdx.x >> 1) * 64;
    int2 i0a, i0b, i1a, i1b;
    asm volatile("ld.global.nc.v2.u32 {%0,%1}, [%8];\nld.global.nc.v2.u32 {%2,%3}, [%8 + 3328];\nld.global.nc.v2.u32 {%4,%5}, [%8 + 8];\nld.global.nc.v2.u32 {%6,%7}, [%8 + 3336];"
                 : "=r"(i0a.x), "=r"(i0a.y), "=r"(i0b.x), "=r"(i0b.y), "=r"(i1a.x), "=r"(i1a.y), "=r"(i1b.x), "=r"(i1b.y)
                 : "l"(idx + (pb0 + b) * NF));
    const uint32_t sb = __shfl_sync(0xffffffffu, smem_u32(smem_raw), 0);
    const uint32_t bars = sb + OFF_BAR;
#define BAR(i) (bars + (i) * 8)
    const int warp = __shfl_sync(0xffffffffu, tid >> 5, 0), lane = tid & 31, g = lane >> 2, t = lane & 3;
    const int rank = blockIdx.x & 1;
    if (tid == 0) TS(0);
    if (elect_one()) {
        mbar_init(BAR(B_PAIR + warp), warp < 13 ? 256 + (warp == 10) : 1);
        if (warp >= 13) {
            asm volatile("fence.mbarrier_init.release.cluster;" ::: "memory");
            mbar_expect_tx(BAR(B_PAIR + warp), warp == 13 ? 64 * NF * 4 : 6 * 32 * 4);
            if (warp == 13) bulk_load(sb + OFF_IDX, idx + pb0 * NF, 64 * NF * 4, BAR(B_IDX));
        }
        if (warp == 6) asm volatile("cp.async.bulk.prefetch.L2.global [%0], %1;" ::"l"((const char*)w1 + 4 * 32768 + blockIdx.x * 5632), "n"(5632) : "memory");
        mbar_init(BAR(16 + warp), ((0xAAAC >> warp) & 1) ? 9 : 1);
        mbar_init(BAR(32 + warp), (warp & 1) ? 9 : 1);
        mbar_init(BAR(48 + warp), 4);
        mbar_init(BAR(64 + warp), warp == B_CDONE - 64 ? 8 : 4);
        if (warp < 6) mbar_init(BAR(warp), warp < 4 ? (0x2321 >> (4 * warp)) & 3 : 256);
        asm volatile("fence.mbarrier_init.release.cluster;" ::: "memory");
    }
    __syncthreads();
    asm volatile("barrier.cluster.arrive.relaxed.aligned;" ::: "memory");
    if (tid == 0) TS(1);

    if (warp >= 12) {
        asm volatile("setmaxnreg.dec.sync.aligned.u32 %0;" ::"n"(R_PROD));
        if ((sb & 0xFFFFFFu) != SB0) __trap();
        if (warp == 12) {
#pragma unroll 1
            for (int f = 0; f < NF; f++) {
                if (f >= 4) mbar_wait_bounded(BAR(B_EMPTY + f - 4), 0);
                TSL(80 + f);
                if (elect_one()) {
                    mbar_expect_tx(BAR(B_W + f), HS_BYTES);
                    tma_load_3d(sb + OFF_RING + ((f + 2) & 3) * HS_BYTES, &tmW1, 0, f * 64, rank * 2, BAR(B_W + f));
                }
            }
            asm volatile("barrier.cluster.wait.acquire.aligned;" ::: "memory");
            const uint64_t po = (uint64_t)(out + pb0 + 32 * rank + lane);
            const uint32_t plo = opq((uint32_t)po), phi = opq((uint32_t)(po >> 32) + (lane >> 5)), dp = opq(sb + OFF_DP + lane * 4);
            mbar_wait_bounded(BAR(B_FIN), 0);
            const uint4 u = make_uint4(lds32(dp), lds32(dp + 128), lds32(dp + 256), lds32(dp + 384));
            const uint2 v = make_uint2(lds32(dp + 512), lds32(dp + 640));
            asm volatile("st.global.u16 [%0], %1;" ::"l"(((uint64_t)phi << 32) | plo),
                         "h"(__bfloat16_as_ushort(__float2bfloat16_rn((__uint_as_float(u.x) + __uint_as_float(u.y)) + (__uint_as_float(u.z) + __uint_as_float(u.w)) +
                                                                      (__uint_as_float(v.x) + __uint_as_float(v.y)))))
                         : "memory");
            TSL(15);
        } else {
            if (warp == 14) {
#pragma unroll 1
                for (int k = JIT; k < NF; k++) {
                    mbar_wait(BAR(B_PAIR + min((k + 3) >> 1, 12)), 0);
                    mbar_wait(BAR(B_W + k), 0);
                    asm volatile("bar.arrive %0, 160;" ::"r"(4 + (k & 3)) : "memory");
                }
            } else if (warp == 13) {
                const uint32_t sr = sb + OFF_AP;
                {
                    uint32_t v[12];
#pragma unroll
                    for (int i = 0; i < 12; i++) v[i] = lane + 32 * (i >> 1) < NF * NFR / 2 ? __ldg(reinterpret_cast<const uint32_t*>((i & 1) ? se_w2 : se_w1) + lane + 32 * (i >> 1)) : 0u;
#pragma unroll
                    for (int i = 0; i < 12; i++) asm volatile("st.shared.u32 [%0], %1;" ::"r"(sr + lane * 4 + (i >> 1) * 128 + (i & 1) * 1024), "r"(v[i]) : "memory");
                    __syncwarp();
                }
#pragma unroll 1
                for (int q = 0; q < 8; q++) {
                    const int c1 = 8 * (q & 1) + g, o1 = c1 < NFR ? min((8 * (q >> 1) + 2 * t) * NFR + c1, NF * NFR) : NF * NFR;
                    const int c2 = 8 * (q & 3) + ((q & 3) < 3 ? 4 * (g & 1) + (g >> 1) : (g & 1)), o2 = min((8 * (q >> 2) + 2 * t) * NF + c2, NF * NFR);
                    uint32_t y1, y2;
                    asm volatile("{\n.reg .b16 a, b, c, d;\nld.shared.b16 a, [%2];\nld.shared.b16 b, [%2 + 26];\nld.shared.b16 c, [%3 + 1024];\nld.shared.b16 d, [%3 + 1076];\n"
                                 "mov.b32 %0, {a, b};\nmov.b32 %1, {c, d};\n}\n" : "=r"(y1), "=r"(y2) : "r"(sr + 2 * o1), "r"(sr + 2 * o2));
                    asm volatile("st.shared.u32 [%0], %1;\nst.shared.u32 [%0 + 1024], %2;" ::"r"(sb + OFF_SEF + q * 128 + lane * 4), "r"(y1),
                                 "r"(hmul2_bf16(y2, 0x3E803E80u))
                                 : "memory");
                }
                fence_proxy_async();
                __syncwarp();
                TSL(12);
                if (elect_one()) mbar_arrive(BAR(B_PAIR + 10));
            } else {
                {
                    const int pq = blockIdx.x >> 6, js = (blockIdx.x >> 1) & 31;
                    const int j = js < 24 ? (js & 24) + 4 * (js & 1) + ((js >> 1) & 3) : 24 + (js & 1);
                    const bool on = js < 24 || ((js >> 1) & 3) == ((lane >> 2) & 3);
                    const __nv_bfloat16* s = w_cross + ((size_t)(pq * NF) * NF + j) * ND + 32 * rank + lane;
                    uint8_t* d = g_wt + (size_t)rank * NCHUNK * CHUNK + (((lane & 15) >> 1) * 2 + (lane >> 4)) * CHUNK + ((lane & 1) * 2 + pq) * TILE + js * 16;
#pragma unroll 1
                    for (int kh = 0; kh < 2; kh++) {
                        uint32_t x[8];
#pragma unroll
                        for (int k = 0; k < 8; k++)
                            x[k] = (on && (kh == 0 || k < 5)) ? ldg_u16(s + (k + (k & 4)) * NF * ND) | (ldg_u16(s + (k == 4 && kh ? 9 : k + (k & 4) + 4) * NF * ND) << 16) : 0u;
                        *reinterpret_cast<uint4*>(d) = make_uint4(x[0], x[1], x[2], x[3]);
                        *reinterpret_cast<uint4*>(d + 512) = make_uint4(x[4], x[5], x[6], x[7]);
                        s += 16 * NF * ND;
                        d += 1024;
                    }
                    __syncwarp();
                }
                TSL(8);
                if (elect_one()) asm volatile("red.release.gpu.global.inc.u32 [%0], %1;" ::"l"(&g_cnt), "n"(NUNIT + 127) : "memory");
                TSL(9);
                mbar_wait(BAR(B_EMPTY + 6), 0);
                TSL(10);
                unsigned int v;
                do {
                    asm volatile("ld.acquire.gpu.global.u32 %0, [%1];" : "=r"(v) : "l"(&g_cnt) : "memory");
                } while (v < NUNIT);
                asm volatile("fence.proxy.async.global;" ::: "memory");
                __syncwarp();
                if (elect_one()) asm volatile("red.relaxed.gpu.global.inc.u32 [%0], %1;" ::"l"(&g_cnt), "n"(NUNIT + 127) : "memory");
                TSL(11);
                const uint8_t* wsrc = g_wt + (size_t)rank * NCHUNK * CHUNK;
#pragma unroll 1
                for (int k = 0; k < 8; k++) {
                    mbar_wait(BAR(B_EMPTY + 20 + ((0x75493260 >> (4 * k)) & 15)), 0);
                    TSL(30 + k);
                    if (elect_one()) {
                        const uint32_t cf = BAR(B_CFULL + ((0x33222110 >> (4 * k)) & 3));
                        mbar_expect_tx(cf, 2 * CHUNK);
                        bulk_load(sb + OFF_TW + ((CPOS >> (4 * k)) & 7) * 2 * CHUNK, wsrc + k * 2 * CHUNK, 2 * CHUNK, cf);
                    }
                }
            }
            __syncwarp();
            asm volatile("barrier.cluster.wait.acquire.aligned;" ::: "memory");
        }
    } else if (warp < 4) {
        {
            const uint4* wb = reinterpret_cast<const uint4*>(w_bi + (tid >> 2) * 64 + 32 * rank + 8 * t);
            const uint4 wb0 = __ldg(wb), wb1 = __ldg(wb + 256);
            const uint32_t w2v = __ldg(reinterpret_cast<const uint32_t*>(w2) + rank * 64 + (tid & 63));
            sts128(sb + OFF_WBI + (tid & 63) * 128 + ((4 ^ (tid & 7)) << 4), 0x3C803C80u, 0x3C803C80u, 0x3C803C80u, 0x3C803C80u);
            asm volatile("st.shared.u32 [%0], %1;" ::"r"(sb + OFF_ID + (tid & 63) * 4), "r"(0x3F803F80u) : "memory");
            asm volatile("st.shared.u32 [%0], %1;" ::"r"(sb + OFF_W2 + (tid & 56) * 4 + (tid & 3) * 8 + (tid & 4)), "r"(w2v) : "memory");
            const uint32_t wd = sb + OFF_WBI + (tid >> 2) * 128 + ((t ^ (g & 7)) << 4);
            sts128(wd, wb0.x, wb0.y, wb0.z, wb0.w);
            sts128(wd + 4096, wb1.x, wb1.y, wb1.z, wb1.w);
            fence_proxy_async();
        }
        asm volatile("setmaxnreg.inc.sync.aligned.u32 %0;" ::"n"(R_DEEP));
        asm volatile("bar.sync 1, 128;" ::: "memory");
        asm volatile("barrier.cluster.wait.acquire.aligned;" ::: "memory");
        TS(7);
        float acc[64];
        float e2[2][20];
#pragma unroll
        for (int i = 0; i < 64; i++) asm volatile("" : "=f"(acc[i]));
#pragma unroll
        for (int i = 0; i < 20; i++) asm volatile("" : "=f"(e2[0][i]), "=f"(e2[1][i]));
        uint32_t A[4][4][4];
        constexpr uint64_t dr = make_desc(SB0 + OFF_RING, 8192, 1024, 1), dwc = make_desc(SB0 + OFF_WBI, 4096, 1024, 1);
        const uint64_t dw = uni64(dwc + (sb >> 28));
        const uint32_t sa = opq((lane >> 4) * 128 + (2 * warp + ((lane >> 3) & 1)) * 512 + (lane & 7) * 16);
        const uint32_t ln = opq(lane);
        const bool l0 = ln == 0;
        uint32_t la[4];
#pragma unroll
        for (int i = 0; i < 4; i++) la[i] = opq((sb + OFF_RT + (16 * warp + (lane & 15)) * 128 + (((lane >> 4) ^ (lane & 7)) << 4)) ^ (i << 5));
        uint32_t za[8];
#pragma unroll
        for (int i = 0; i < 6; i++) asm volatile("" : "=r"(za[i]));
        auto cvt = [&](uint32_t (&pk)[8], int f) {
            const float(&e)[20] = e2[f & 1];
#pragma unroll
            for (int i = 0; i < 8; i++) asm volatile("cvt.rn.bf16x2.f32 %0, %1, %2;" : "=r"(pk[i]) : "f"(e[2 * i + 1]), "f"(e[2 * i]));
            uint32_t &z0 = za[2 * (f >> 3)], &z1 = za[2 * (f >> 3) + 1];
            asm volatile("{\n.reg .pred p;\nsetp.eq.u32 p, %6, %7;\n@p cvt.rn.bf16x2.f32 %0, %2, %4;\n@p cvt.rn.bf16x2.f32 %1, %3, %5;\n}\n"
                         : "+r"(z0), "+r"(z1)
                         : "f"(e[16]), "f"(e[18]), "f"((f & 1) ? __uint_as_float(z0) : 0.f), "f"((f & 1) ? __uint_as_float(z1) : 0.f), "r"(ln & 3), "r"((f >> 1) & 3));
        };
        auto store = [&](const uint32_t (&pk)[8], int f) {
            stsm_x4_t(sa + sb + OFF_EW + f * EWP, pk[0], pk[1], pk[2], pk[3]);
            stsm_x4_t(sa + sb + OFF_EW + f * EWP + 256, pk[4], pk[5], pk[6], pk[7]);
        };
        auto load1 = [&](auto VC, int i, uint32_t o) {
            constexpr int v = decltype(VC)::value;
            ldsm_x4(la[i ^ (2 * (v & 1))] + o, A[v][i][0], A[v][i][1], A[v][i][2], A[v][i][3]);
        };
        auto mma_e = [&](auto VC) {
            constexpr int v = decltype(VC)::value;
            uint32_t(&ai)[4][4] = A[v];
            wgmma_m64n40k16_rs_tb<2>(e2[v & 1], ai[0], dw);
            wgmma_m64n40k16_rs_tb<1>(e2[v & 1], ai[1], dw + 128);
            wgmma_m64n40k16_rs_tb<1>(e2[v & 1], ai[2], dw + 256);
            wgmma_m64n40k16_rs_tb<1>(e2[v & 1], ai[3], dw + 384);
        };
        auto mma_d1 = [&](auto VC, int i, int sc) {
            constexpr int v = decltype(VC)::value, st = (v + 2) & 3;
            wgmma_m64n128k16_rs_tb(acc, A[v][i], dr + st * (HS_BYTES >> 4) + 128 * i, sc);
        };
        auto mma_d = [&](auto VC, int sc) {
            wgmma_fence();
#pragma unroll
            for (int i = 0; i < 4; i++) mma_d1(VC, i, i ? 1 : sc);
            wgmma_commit();
        };
        auto mma_e1 = [&](auto VC) {
            wgmma_fence();
            mma_e(VC);
            wgmma_commit();
        };
        auto load = [&](auto VC, uint32_t o) {
#pragma unroll
            for (int i = 0; i < 4; i++) load1(VC, i, o);
        };
#define READY(k) asm volatile("bar.sync %0, 160;" ::"n"(4 + ((k) & 3)) : "memory")
        using I0 = std::integral_constant<int, 0>;
        using I1 = std::integral_constant<int, 1>;
        using I2 = std::integral_constant<int, 2>;
        using I3 = std::integral_constant<int, 3>;
        uint32_t pk[8];
        mbar_wait(BAR(B_F), 0);
        TS(19);
        load(I0{}, 0);
        static_for<0, JIT>([&](auto KC) {
            constexpr int k = decltype(KC)::value;
            std::integral_constant<int, k & 3> UC;
            if (k > 1) cvt(pk, k - 2);
            mma_e1(UC);
            mbar_wait(BAR(B_W + k), 0);
            mma_d(UC, k);
            wgmma_wait<2>();
            if (k > 0 && l0) mbar_arrive(BAR(B_EMPTY + k - 1));
            if (k > 1) store(pk, k - 2);
            mbar_wait(BAR(((k & 1) && k < JIT - 1 ? B_F : B_PAIR) + (k + 1) / 2), 0);
            load(std::integral_constant<int, (k + 1) & 3>{}, ((k + 1 + 11 * (~k & 1)) / 2) * RT);
        });
        load(std::integral_constant<int, (JIT + 1) & 3>{}, ((JIT + 12) / 2) * RT);
        mbar_wait(BAR(B_PAIR + JIT / 2 + 1), 0);
        TS(20);
        static_for<JIT, 22>([&](auto KC) {
            constexpr int k = decltype(KC)::value;
            std::integral_constant<int, k & 3> UC;
            cvt(pk, k - 2);
            store(pk, k - 2);
            load(std::integral_constant<int, (k & 3) ^ 2>{}, ((k + 2 + 11 * (k & 1)) / 2) * RT);
            mma_e1(UC);
            READY(k);
            mma_d(UC, 1);
            wgmma_wait<2>();
            if (l0) mbar_arrive(BAR(B_EMPTY + k - 1));
        });
        {
            uint32_t p2[8];
            cvt(pk, 20);
            store(pk, 20);
            load(I0{}, 12 * RT);
            mma_e1(I2{});
            wgmma_wait<2>();
            cvt(pk, 21);
            mma_e1(I3{});
            store(pk, 21);
            READY(22);
            READY(23);
            wgmma_wait<2>();
            if (l0) mbar_arrive(BAR(B_EMPTY + 21));
            load(I1{}, 13 * RT);
            wgmma_wait<1>();
            cvt(pk, 22);
            mma_e1(I0{});
            store(pk, 22);
            wgmma_wait<1>();
            cvt(pk, 23);
            mma_e1(I1{});
            auto mma_h = [&](auto VC, int hh) {
                mma_d1(VC, 2 * hh, 1);
                mma_d1(VC, 2 * hh + 1, 1);
                wgmma_commit();
            };
            mma_h(I2{}, 0);
            store(pk, 23);
            wgmma_wait<1>();
            if (l0) mbar_arrive(BAR(B_ZRDY));
            TS(2);
            za[6] = za[7] = 0u;
            cvt(pk, 24);
            cvt(p2, 25);
#pragma unroll
            for (int i = 0; i < 6; i++) za[i] |= p2[7] & (ln >> 5);
            constexpr uint64_t d1 = make_desc(SB0 + OFF_SEF, 256, 128, 0), d2 = make_desc(SB0 + OFF_SEF + 1024, 512, 128, 0);
            float h[8], o[16];
#pragma unroll
            for (int i = 0; i < 16; i++) asm volatile("" : "=f"(o[i]), "=f"(h[i & 7]));
            wgmma_fence();
            wgmma_m64n16k16_rs<0>(h, za, d1);
            wgmma_m64n16k16_rs<1>(h, za + 4, d1 + 32);
            wgmma_commit();
            mma_h(I2{}, 1);
            mma_d(I3{}, 1);
            wgmma_wait<2>();
            const uint32_t ha0 = pack_bf16(gelu2(h[0]), gelu2(h[1])), ha1 = pack_bf16(gelu2(h[2]), gelu2(h[3])), ha2 = pack_bf16(gelu2(h[4]), gelu2(h[5])),
                           ha3 = pack_bf16(gelu2(h[6]), gelu2(h[7]));
            wgmma_fence();
            wgmma_m64n32k16_rs<2>(o, ha0, ha1, ha2, ha3, d2);
            wgmma_commit();
            wgmma_wait<2>();
            if (l0) mbar_arrive(BAR(B_EMPTY + 22));
            READY(24);
            mma_d(I0{}, 1);
            READY(25);
            store(pk, 24);
            store(p2, 25);
            wgmma_wait<1>();
            if (l0) mbar_arrive(BAR(B_EMPTY + 23));
            mma_d(I1{}, 1);
#pragma unroll
            for (int i = 0; i < 2; i++) {
                uint32_t a[4];
#pragma unroll
                for (int k = 0; k < 4; k++) a[k] = pack_bf16(fmaf(tanh_fast(o[8 * i + 2 * k]), 0.5f, 0.5f), fmaf(tanh_fast(o[8 * i + 2 * k + 1]), 0.5f, 0.5f));
                sts128(sb + OFF_AP + i * 2048 + warp * 512 + ln * 16, a[0], a[1], a[2], a[3]);
            }
            __syncwarp();
            if (l0) mbar_arrive(BAR(B_EWRDY));
            wgmma_wait<1>();
            if (l0) mbar_arrive(BAR(B_EMPTY + 24));
            TS(3);
        }
        {
            wgmma_wait<0>();
            if (l0) mbar_arrive(BAR(B_EMPTY + 25));
            uint32_t hw[32];
#pragma unroll
            for (int i = 0; i < 32; i++) asm volatile("cvt.rn.bf16x2.f32 %0, %1, %2;" : "=r"(hw[i]) : "f"(acc[2 * i + 1]), "f"(acc[2 * i]));
            asm volatile("setmaxnreg.dec.sync.aligned.u32 %0;" ::"n"(R_DEEP2));
            TS(4);
            float o[4] = {0.f, 0.f, 0.f, 0.f};
            int l2;
            asm volatile("mov.u32 %0, %%laneid;" : "=r"(l2));
#pragma unroll
            for (int it = 0; it < 8; it++) {
                uint32_t b0, b1;
                asm volatile("ld.shared.v2.u32 {%0,%1}, [%2];" : "=r"(b0), "=r"(b1) : "r"(sb + OFF_W2 + 8 * (l2 & 3) + it * 32));
                mma16816(o, gelu2p(hw[4 * it]), gelu2p(hw[4 * it + 1]), gelu2p(hw[4 * it + 2]), gelu2p(hw[4 * it + 3]), b0, b1);
            }
            uint32_t da, db, tt;
            send_addr(sb, rank * 3, warp, da, db, tt);
            send_partial(da, db, tt, 0.5f * o[0], 0.5f * o[2]);
        }
        TS(5);
    } else {
        const int wgc = (warp >> 2) - 1, w4 = warp & 3;
        const char* so = (const char*)table + 16 * (lane & 7);
        auto rp = [&](uint32_t i) { return row_ptr(so, i); };
        const uint32_t d0 = opq(sb + OFF_RT + b * 128 + (((lane ^ b) & 7) << 4)), d1 = opq((d0 ^ 64) + 6 * RT);
        uint32_t c0;
        auto until = [&](int f) {
            for (;;) {
                uint32_t c;
                asm volatile("mov.u32 %0, %%clock;" : "=r"(c)::"memory");
                if (c - c0 >= f * 300) break;
                __nanosleep(32);
            }
        };
        {
            const int ia[4] = {i0a.x, i0a.y, i1a.x, i1a.y}, ib[4] = {i0b.x, i0b.y, i1b.x, i1b.y};
            static_for<0, NFIRST>([&](auto FC) {
                constexpr int f = decltype(FC)::value, o = (f >> 1) * RT;
                if (f) until(f);
                cp_async16(((f & 1) ? d1 : d0) + o, rp(ia[f]));
                cp_async16(((f & 1) ? d1 : d0) + o + 4096, rp(ib[f]));
                cp_async_mbar_arrive_noinc(BAR(((f & 1) ? B_PAIR : B_F) + (f >> 1)));
                if (f == 0) asm volatile("mov.u32 %0, %%clock;" : "=r"(c0)::"memory");
            });
            if (wgc == 0) TS(6);
        }
        asm volatile("setmaxnreg.inc.sync.aligned.u32 %0;" ::"n"(R_CR1));
        uint32_t M[8][12], y[4][2];
        {
            const uint32_t pa = opq(sb + OFF_RT + (t & 1) * 6 * RT + (16 * w4 + g) * 128 + (((4 * rank + 2 * wgc) ^ g ^ (4 * (t & 1))) << 4)), t1 = opq(t >> 1);
            const uint32_t ia = opq(sb + OFF_IDX + b * NF * 4);
#pragma unroll
            for (int i = 0; i < 96; i++) asm volatile("" : "=r"(M[i / 12][i % 12]));
            mbar_wait(BAR(B_IDX), 0);
            uint32_t x[13][4];
#pragma unroll
            for (int p = 2; p < 13; p++)
                asm volatile("ld.shared.v2.u32 {%0,%1}, [%4];\nld.shared.v2.u32 {%2,%3}, [%4 + 3328];" : "=r"(x[p][0]), "=r"(x[p][2]), "=r"(x[p][1]), "=r"(x[p][3]) : "r"(ia + p * 8));
            const uint32_t pb = opq(pa ^ 16);
            auto conv = [&](int G) {
#pragma unroll
                for (int i = 0; i < 16; i++) {
                    uint32_t &u = M[i >> 1][4 * G + 2 * (i & 1)], &v = M[i >> 1][4 * G + 2 * (i & 1) + 1];
                    asm volatile("{\n.reg .b32 t;\nprmt.b32 t, %0, %1, 0x5410;\nprmt.b32 %1, %0, %1, 0x7632;\nmov.b32 %0, t;\n}\n" : "+r"(u), "+r"(v));
                }
#pragma unroll
                for (int i = 0; i < 8; i++)
                    asm volatile("{\n.reg .pred p;\nsetp.eq.u32 p, %5, 2;\n@p st.shared.v4.u32 [%4], {%0,%1,%2,%3};\n}\n" ::"r"(M[i & 4][4 * G + (i & 3)]), "r"(M[(i & 4) + 1][4 * G + (i & 3)]),
                                 "r"(M[(i & 4) + 2][4 * G + (i & 3)]), "r"(M[(i & 4) + 3][4 * G + (i & 3)]), "r"(pa), "r"(t1));
            };
            auto gather = [&](auto PC) {
                constexpr int p = decltype(PC)::value;
                constexpr uint32_t o1 = (p < 12 ? p : 7) * RT;
                if (p < 6) until(2 * p);
                cp_async16(d0 + p * RT, rp(x[p][0]));
                cp_async16(d0 + p * RT + 4096, rp(x[p][1]));
                if (p < 6) until(2 * p + 1);
                cp_async16(d1 + o1, rp(x[p][2]));
                cp_async16(d1 + o1 + 4096, rp(x[p][3]));
                cp_async_mbar_arrive_noinc(BAR(B_PAIR + p));
            };
            auto pick = [&](auto QC) {
                constexpr int q = decltype(QC)::value, c = 4 * (q >> 2) + ((q >> 1) & 1);
#pragma unroll
                for (int i = 0; i < 4; i++)
                    asm volatile("{\n.reg .pred p;\nsetp.eq.u32 p, %5, %6;\n@p ld.shared.v4.u32 {%0,%1,%2,%3}, [%4];\n}\n"
                                 : "+r"(M[2 * (i & 2)][c + 2 * (i & 1)]), "+r"(M[2 * (i & 2) + 1][c + 2 * (i & 1)]), "+r"(M[2 * (i & 2) + 2][c + 2 * (i & 1)]),
                                   "+r"(M[2 * (i & 2) + 3][c + 2 * (i & 1)])
                                 : "r"(((i & 2) ? pb : pa) + q * RT + (i & 1) * 1024), "r"(t1), "n"(q & 1));
                __syncwarp();
                if (elect_one()) mbar_arrive(BAR(B_W + 2 * q + 1 + (q == 0)));
                if (q == 4 || q == 8) conv(q / 4 - 1);
            };
#define IC(x) std::integral_constant<int, x>{}
            gather(IC(2));
            gather(IC(3));
            static_for<0, 3>([&](auto QC) {
                constexpr int q = decltype(QC)::value;
                mbar_wait(BAR(B_PAIR + q), 0);
                pick(QC);
                if constexpr (q < 2) gather(IC(q + 4));
            });
            static_for<3, 12>([&](auto QC) {
                constexpr int q = decltype(QC)::value, p = q < 9 ? q + 3 : q == 10 ? 12 : 0;
                mbar_wait(BAR(B_EMPTY + 2 * q - 6 + (q == 3)), 0);
                mbar_wait(BAR(B_PAIR + q), 0);
                if constexpr (p) gather(IC(p));
                pick(QC);
            });
            const uint32_t ta = sb + OFF_RT + 12 * RT + (16 * w4 + g) * 128 + (((4 * rank + 2 * wgc + (t >> 1)) ^ g) << 4) + 8 * (t & 1);
            mbar_wait(BAR(B_PAIR + 12), 0);
#pragma unroll
            for (int k = 0; k < 4; k++) asm volatile("ld.shared.v2.u32 {%0,%1}, [%2];" : "=r"(y[k][0]), "=r"(y[k][1]) : "r"(((k & 1) ? (ta ^ 64) + RT : ta) + (k >> 1) * 1024));
            __syncwarp();
            if (elect_one()) mbar_arrive(BAR(B_W + 25));
            conv(2);
        }
        uint32_t TL[4][2];
        uint32_t ap[8], a0, a1;
        uint32_t A0[8], A1[8], Aq[8], w[8], aq;
        {
            const int r = lane & 7, bh = (lane >> 3) & 1, ig = lane >> 4;
            const uint32_t x = sb + OFF_EW + wgc * 256 + (2 * w4 + bh) * 512 + (8 * ig + 4 * (r & 1) + (r >> 1)) * EWP;
            a0 = opq(x);
            a1 = opq(x + (!ig || r == 0 ? 16 : r == 1 ? 13 : r == 2 ? 11 : 8) * EWP);
            aq = opq(sb + OFF_AP + w4 * 512 + lane * 16);
        }
        asm volatile("barrier.cluster.wait.acquire.aligned;" ::: "memory");
        mbar_wait(BAR(B_CFULL), 0);
        mbar_wait(BAR(B_EWRDY), 0);
        u_lda(A0, a0, a1);
#pragma unroll
        for (int i = 0; i < 2; i++) {
            const uint4 v = lds128(aq + i * 2048);
            ap[4 * i] = v.x, ap[4 * i + 1] = v.y, ap[4 * i + 2] = v.z, ap[4 * i + 3] = v.w;
        }
        if (wgc == 0) TS(60);
        asm volatile("setmaxnreg.inc.sync.aligned.u32 %0;" ::"n"(R_CR2));
        if (wgc == 0) TS(61);
        asm volatile("mov.u32 %0, %%clock;\nand.b32 %0, %0, %1;" : "=r"(aq) : "r"(warp >> 4));
        a0 |= aq, a1 |= aq;
#pragma unroll
        for (int k = 0; k < 8; k++) {
            TL[k >> 1][k & 1] = __byte_perm(y[2 * (k & 1)][k >> 2], y[2 * (k & 1) + 1][k >> 2], (0x5410 + 0x2222 * ((k >> 1) & 1)) | aq);
            ap[k] |= aq, A0[k] |= aq & TL[k >> 1][k & 1];
        }
        constexpr uint64_t dt = make_desc(SB0 + OFF_TW, 512, 128, 0), dqc = make_desc(SB0 + OFF_ID, 128, 128, 0);
        const uint64_t dq = uni64(dqc + (sb >> 28));
        const uint64_t desc = dt + wgc * (CHUNK >> 4);
        auto dsc = [&](int e, int pq) { return desc + ((CPOS >> (4 * (e >> 1))) & 7) * (2 * CHUNK >> 4) + ((e & 1) * 2 + pq) * (TILE >> 4); };
        float S[4], accP[16], accQ[16];
#pragma unroll
        for (int i = 0; i < 16; i++) asm volatile("" : "=f"(accP[i]), "=f"(accQ[i]));
        u_lda(A1, a0 + 16, a1 + 16);
#pragma unroll
        for (int i = 0; i < 4; i++) asm volatile("" : "=f"(S[i]));
#pragma unroll
        for (int k = 0; k < 8; k++) Aq[k] = hmul2_bf16(A0[k], ap[k]);
        wgmma_fence();
        u_mma(accP, A0, dsc(0, 0));
        wgmma_commit();
        u_mma(accQ, Aq, dsc(0, 1));
        wgmma_commit();
        if (wgc == 0) TS(62);
        auto pack8 = [&](uint32_t (&d)[8], const float (&a)[16]) {
#pragma unroll
            for (int k = 0; k < 8; k++) asm volatile("cvt.rn.bf16x2.f32 %0, %1, %2;" : "=r"(d[k]) : "f"(a[2 * k + 1]), "f"(a[2 * k]));
        };
        uint32_t da, db, tt;
        static_for<0, 8>([&](auto PC) {
            constexpr int p = decltype(PC)::value, e = 2 * p;
            if (p == 7) send_addr(sb, rank * 3 + 1 + wgc, w4, da, db, tt);
            auto mw = [&](int s, int k) { return k < 6 ? M[p][2 * k + s] : TL[(e + s) & 3][k - 6]; };
            uint32_t tp[8], tq[8];
            wgmma_wait<1>();
            pack8(tp, accP);
            wgmma_fence();
            u_mma(accP, A1, dsc(e + 1, 0));
            if (p) {
                wgmma_m64n8k16_rs(S, w, dq, p > 1);
                wgmma_m64n8k16_rs(S, w + 4, dq, 1);
            }
            wgmma_commit();
            if (p < 7) u_lda(A0, a0 + 16 * e + 32, a1 + 16 * e + 32);
            wgmma_wait<1>();
            pack8(tq, accQ);
#pragma unroll
            for (int k = 0; k < 8; k++) Aq[k] = hmul2_bf16(A1[k], ap[k]);
            wgmma_fence();
            u_mma(accQ, Aq, dsc(e + 1, 1));
            wgmma_commit();
#pragma unroll
            for (int k = 0; k < 8; k++) tq[k] = hfma2_bf16(tq[k], ap[k], tp[k]);
            if (p == 0 || p == 2 || p == 5) mbar_wait(BAR(B_CFULL + 1 + p / 2), 0);
            wgmma_wait<1>();
            pack8(tp, accP);
            if (p < 7) {
                wgmma_fence();
                u_mma(accP, A0, dsc(e + 2, 0));
                wgmma_commit();
                u_lda(A1, a0 + 16 * e + 48, a1 + 16 * e + 48);
            }
#pragma unroll
            for (int k = 0; k < 8; k++) w[k] = hmul2_bf16(tq[k], mw(0, k));
            wgmma_wait<(p < 7)>();
            if (p == 0 && elect_one()) mbar_arrive(BAR(B_CDONE));
            pack8(tq, accQ);
            if (p < 7) {
#pragma unroll
                for (int k = 0; k < 8; k++) Aq[k] = hmul2_bf16(A0[k], ap[k]);
                wgmma_fence();
                u_mma(accQ, Aq, dsc(e + 2, 1));
                wgmma_commit();
            }
#pragma unroll
            for (int k = 0; k < 8; k++) w[k] = hfma2_bf16(hfma2_bf16(tq[k], ap[k], tp[k]), mw(1, k), w[k]);
        });
        wgmma_fence();
        wgmma_m64n8k16_rs(S, w, dq, 1);
        wgmma_m64n8k16_rs(S, w + 4, dq, 1);
        wgmma_commit();
        wgmma_wait<0>();
        send_partial(da, db, tt, S[0], S[2]);
        if (wgc == 0) TS(14);
    }
#undef BAR
}

typedef CUresult (*PFN_encodeTiled)(CUtensorMap*, CUtensorMapDataType, cuuint32_t, void*, const cuuint64_t*, const cuuint64_t*,
                                    const cuuint32_t*, const cuuint32_t*, CUtensorMapInterleave, CUtensorMapSwizzle,
                                    CUtensorMapL2promotion, CUtensorMapFloatOOBfill);

}

extern "C" void kernel_launch(void* const* d_in, const int* in_sizes, int n_in, void* d_out, int out_size) {
    const int* idx = (const int*)d_in[0];
    const __nv_bfloat16* table = (const __nv_bfloat16*)d_in[1];
    const __nv_bfloat16* se_w1 = (const __nv_bfloat16*)d_in[2];
    const __nv_bfloat16* se_w2 = (const __nv_bfloat16*)d_in[3];
    const __nv_bfloat16* w_bi = (const __nv_bfloat16*)d_in[4];
    const __nv_bfloat16* w_cross = (const __nv_bfloat16*)d_in[5];
    const __nv_bfloat16* w_deep1 = (const __nv_bfloat16*)d_in[6];
    const __nv_bfloat16* w_deep2 = (const __nv_bfloat16*)d_in[7];
    __nv_bfloat16* out = (__nv_bfloat16*)d_out;

    static PFN_encodeTiled enc = nullptr;
    if (!enc) {
        void* fn = nullptr;
        cudaDriverEntryPointQueryResult qres;
        cudaGetDriverEntryPoint("cuTensorMapEncodeTiled", &fn, cudaEnableDefault, &qres);
        enc = (PFN_encodeTiled)fn;
        cudaFuncSetAttribute(fused_kernel, cudaFuncAttributeMaxDynamicSharedMemorySize, SMEM);
    }
    CUtensorMap tm;
    {
        cuuint64_t gdim[3] = {64, (cuuint64_t)(NF * ND), 4};
        cuuint64_t gstr[2] = {(cuuint64_t)NH * 2, 128};
        cuuint32_t box[3] = {64, 64, 2};
        cuuint32_t estr[3] = {1, 1, 1};
        enc(&tm, CU_TENSOR_MAP_DATA_TYPE_BFLOAT16, 3, (void*)w_deep1, gdim, gstr, box, estr, CU_TENSOR_MAP_INTERLEAVE_NONE,
            CU_TENSOR_MAP_SWIZZLE_128B, CU_TENSOR_MAP_L2_PROMOTION_L2_256B, CU_TENSOR_MAP_FLOAT_OOB_FILL_NONE);
    }
    fused_kernel<<<128, 512, SMEM>>>(idx, table, w_deep1, w_bi, w_deep2, w_cross, se_w1, se_w2, out, tm);
}
```

```cpp
#include <cuda_runtime.h>
#include <cuda_bf16.h>
#include <cuda.h>
#include <stdint.h>
#include <type_traits>
#include <utility>

#define R_DEEP 216
#define R_CR1 136
#define R_CR2 216
#define R_DEEP2 56
#define R_PROD 24

namespace {

constexpr int NF = 26, ND = 64, NH = 256, NFR = 13;

#define TS(slot)
#define TSL(slot)

__device__ __forceinline__ uint32_t smem_u32(const void* p) { return (uint32_t)__cvta_generic_to_shared(p); }
__device__ __forceinline__ void mbar_init(uint32_t bar, uint32_t cnt) {
    asm volatile("mbarrier.init.shared::cta.b64 [%0], %1;" ::"r"(bar), "r"(cnt));
}
__device__ __forceinline__ void mbar_expect_tx(uint32_t bar, uint32_t bytes) {
    asm volatile("mbarrier.arrive.expect_tx.shared::cta.b64 _, [%0], %1;" ::"r"(bar), "r"(bytes) : "memory");
}
__device__ __forceinline__ void mbar_arrive(uint32_t bar) {
    asm volatile("mbarrier.arrive.shared::cta.b64 _, [%0];" ::"r"(bar) : "memory");
}
__device__ __forceinline__ void mbar_wait(uint32_t bar, uint32_t parity) {
    asm volatile(
        "{\n"
        ".reg .pred p;\n"
        "WAIT_%=:\n"
        "mbarrier.try_wait.parity.shared::cta.b64 p, [%0], %1;\n"
        "@p bra.uni DONE_%=;\nbra.uni WAIT_%=;\nDONE_%=:\n"
        "}\n" ::"r"(bar),
        "r"(parity)
        : "memory");
}
__device__ __forceinline__ uint32_t opq(uint32_t x) { return __shfl_xor_sync(0xffffffffu, x, 0); }
__device__ __forceinline__ uint64_t uni64(uint64_t x) {
    uint32_t lo = (uint32_t)x, hi = (uint32_t)(x >> 32);
    asm volatile("shfl.sync.idx.b32 %0, %0, 0, 31, -1;\nshfl.sync.idx.b32 %1, %1, 0, 31, -1;" : "+r"(lo), "+r"(hi));
    return ((uint64_t)hi << 32) | lo;
}
__device__ __forceinline__ bool elect_one() {
    uint32_t r;
    asm volatile("{\n.reg .pred p;\nelect.sync _|p, 0xffffffff;\nselp.u32 %0, 1, 0, p;\n}\n" : "=r"(r));
    return r;
}
__device__ __forceinline__ const void* row_ptr(const void* base, uint32_t i) {
    const void* r;
    asm("mad.wide.u32 %0, %1, 128, %2;" : "=l"(r) : "r"(i), "l"(base));
    return r;
}
__device__ __forceinline__ void mbar_wait_bounded(uint32_t bar, uint32_t parity) {
    asm volatile(
        "{\n"
        ".reg .pred p;\n"
        ".reg .u32 c;\n"
        "mov.u32 c, 0;\n"
        "WAIT_%=:\n"
        "mbarrier.try_wait.parity.shared::cta.b64 p, [%0], %1;\n"
        "@p bra.uni DONE_%=;\n"
        "add.u32 c, c, 1;\n"
        "setp.lt.u32 p, c, 0x400000;\n"
        "@p bra.uni WAIT_%=;\n"
        "trap;\n"
        "DONE_%=:\n"
        "}\n" ::"r"(bar),
        "r"(parity)
        : "memory");
}
__device__ __forceinline__ void cp_async16(uint32_t dst, const void* src) {
    asm volatile("cp.async.cg.shared.global [%0], [%1], 16;" ::"r"(dst), "l"(src) : "memory");
}
__device__ __forceinline__ void cp_async_mbar_arrive_noinc(uint32_t bar) {
    asm volatile("cp.async.mbarrier.arrive.noinc.shared::cta.b64 [%0];" ::"r"(bar) : "memory");
}
__device__ __forceinline__ void tma_load_3d(uint32_t dst, const void* tmap, int c0, int c1, int c2, uint32_t bar) {
    asm volatile(
        "cp.async.bulk.tensor.3d.shared::cluster.global.mbarrier::complete_tx::bytes [%0], [%1, {%3, %4, %5}], [%2];" ::"r"(dst),
        "l"(tmap), "r"(bar), "r"(c0), "r"(c1), "r"(c2)
        : "memory");
}
__device__ __forceinline__ void bulk_load(uint32_t dst, const void* src, uint32_t bytes, uint32_t bar) {
    asm volatile("cp.async.bulk.shared::cluster.global.mbarrier::complete_tx::bytes [%0], [%1], %2, [%3];" ::"r"(dst), "l"(src), "r"(bytes),
                 "r"(bar)
                 : "memory");
}
__device__ __forceinline__ void fence_proxy_async() { asm volatile("fence.proxy.async.shared::cta;" ::: "memory"); }
__device__ __forceinline__ void wgmma_fence() { asm volatile("wgmma.fence.sync.aligned;" ::: "memory"); }
__device__ __forceinline__ void wgmma_commit() { asm volatile("wgmma.commit_group.sync.aligned;" ::: "memory"); }
template <int N> __device__ __forceinline__ void wgmma_wait() { asm volatile("wgmma.wait_group.sync.aligned %0;" ::"n"(N) : "memory"); }

__device__ __forceinline__ void ldsm_x4_t(uint32_t addr, uint32_t& r0, uint32_t& r1, uint32_t& r2, uint32_t& r3) {
    asm volatile("ldmatrix.sync.aligned.m8n8.x4.trans.shared.b16 {%0,%1,%2,%3}, [%4];" : "=r"(r0), "=r"(r1), "=r"(r2), "=r"(r3) : "r"(addr));
}
__device__ __forceinline__ void stsm_x4_t(uint32_t addr, uint32_t r0, uint32_t r1, uint32_t r2, uint32_t r3) {
    asm volatile("stmatrix.sync.aligned.m8n8.x4.trans.shared.b16 [%0], {%1,%2,%3,%4};" ::"r"(addr), "r"(r0), "r"(r1), "r"(r2), "r"(r3) : "memory");
}
__device__ __forceinline__ uint4 lds128(uint32_t addr) {
    uint4 v;
    asm volatile("ld.shared.v4.u32 {%0,%1,%2,%3}, [%4];" : "=r"(v.x), "=r"(v.y), "=r"(v.z), "=r"(v.w) : "r"(addr));
    return v;
}
__device__ __forceinline__ uint32_t lds32(uint32_t addr) {
    uint32_t v;
    asm volatile("ld.shared.u32 %0, [%1];" : "=r"(v) : "r"(addr));
    return v;
}
__device__ __forceinline__ void sts128(uint32_t addr, uint32_t a, uint32_t b, uint32_t c, uint32_t d) {
    asm volatile("st.shared.v4.u32 [%0], {%1,%2,%3,%4};" ::"r"(addr), "r"(a), "r"(b), "r"(c), "r"(d) : "memory");
}
__device__ __forceinline__ void mma16816(float (&c)[4], uint32_t a0, uint32_t a1, uint32_t a2, uint32_t a3, uint32_t b0, uint32_t b1) {
    asm("mma.sync.aligned.m16n8k16.row.col.f32.bf16.bf16.f32 {%0,%1,%2,%3}, {%4,%5,%6,%7}, {%8,%9}, {%0,%1,%2,%3};"
        : "+f"(c[0]), "+f"(c[1]), "+f"(c[2]), "+f"(c[3])
        : "r"(a0), "r"(a1), "r"(a2), "r"(a3), "r"(b0), "r"(b1));
}
__device__ __forceinline__ uint32_t pack_bf16(float lo, float hi) {
    uint32_t r;
    asm("cvt.rn.bf16x2.f32 %0, %1, %2;" : "=r"(r) : "f"(hi), "f"(lo));
    return r;
}
__device__ __forceinline__ uint32_t hmul2_bf16(uint32_t a, uint32_t b) {
    uint32_t r;
    asm("mul.rn.bf16x2 %0, %1, %2;" : "=r"(r) : "r"(a), "r"(b));
    return r;
}
__device__ __forceinline__ float tanh_fast(float x) {
    float r;
    asm("tanh.approx.f32 %0, %1;" : "=f"(r) : "f"(x));
    return r;
}
#define WG_ACC8(c, b) c(acc[b]), c(acc[b + 1]), c(acc[b + 2]), c(acc[b + 3]), c(acc[b + 4]), c(acc[b + 5]), c(acc[b + 6]), c(acc[b + 7])
__device__ __forceinline__ void wgmma_n168(float (&acc)[84], uint64_t da, uint64_t db, int sc) {
    asm volatile("{\n.reg .pred p;\nsetp.ne.b32 p, %86, 0;\nwgmma.mma_async.sync.aligned.m64n168k16.f32.bf16.bf16 {%0,%1,%2,%3,%4,%5,%6,%7,%8,%9,%10,%11,%12,%13,%14,%15,%16,%17,%18,%19,%20,%21,%22,%23,%24,%25,%26,%27,%28,%29,%30,%31,%32,%33,%34,%35,%36,%37,%38,%39,%40,%41,%42,%43,%44,%45,%46,%47,%48,%49,%50,%51,%52,%53,%54,%55,%56,%57,%58,%59,%60,%61,%62,%63,%64,%65,%66,%67,%68,%69,%70,%71,%72,%73,%74,%75,%76,%77,%78,%79,%80,%81,%82,%83}, %84, %85, p, 1, 1, 0, 1;\n}\n"
                 : "+f"(acc[0]), "+f"(acc[1]), "+f"(acc[2]), "+f"(acc[3]), "+f"(acc[4]), "+f"(acc[5]), "+f"(acc[6]), "+f"(acc[7]), "+f"(acc[8]), "+f"(acc[9]), "+f"(acc[10]), "+f"(acc[11]), "+f"(acc[12]), "+f"(acc[13]), "+f"(acc[14]), "+f"(acc[15]), "+f"(acc[16]), "+f"(acc[17]), "+f"(acc[18]), "+f"(acc[19]), "+f"(acc[20]), "+f"(acc[21]), "+f"(acc[22]), "+f"(acc[23]), "+f"(acc[24]), "+f"(acc[25]), "+f"(acc[26]), "+f"(acc[27]), "+f"(acc[28]), "+f"(acc[29]), "+f"(acc[30]), "+f"(acc[31]), "+f"(acc[32]), "+f"(acc[33]), "+f"(acc[34]), "+f"(acc[35]), "+f"(acc[36]), "+f"(acc[37]), "+f"(acc[38]), "+f"(acc[39]), "+f"(acc[40]), "+f"(acc[41]), "+f"(acc[42]), "+f"(acc[43]), "+f"(acc[44]), "+f"(acc[45]), "+f"(acc[46]), "+f"(acc[47]), "+f"(acc[48]), "+f"(acc[49]), "+f"(acc[50]), "+f"(acc[51]), "+f"(acc[52]), "+f"(acc[53]), "+f"(acc[54]), "+f"(acc[55]), "+f"(acc[56]), "+f"(acc[57]), "+f"(acc[58]), "+f"(acc[59]), "+f"(acc[60]), "+f"(acc[61]), "+f"(acc[62]), "+f"(acc[63]), "+f"(acc[64]), "+f"(acc[65]), "+f"(acc[66]), "+f"(acc[67]), "+f"(acc[68]), "+f"(acc[69]), "+f"(acc[70]), "+f"(acc[71]), "+f"(acc[72]), "+f"(acc[73]), "+f"(acc[74]), "+f"(acc[75]), "+f"(acc[76]), "+f"(acc[77]), "+f"(acc[78]), "+f"(acc[79]), "+f"(acc[80]), "+f"(acc[81]), "+f"(acc[82]), "+f"(acc[83])
                 : "l"(da), "l"(db), "r"(sc));
}
__device__ __forceinline__ void wgmma_n128(float (&acc)[64], uint64_t da, uint64_t db, int sc) {
    asm volatile("{\n.reg .pred p;\nsetp.ne.b32 p, %66, 0;\nwgmma.mma_async.sync.aligned.m64n128k16.f32.bf16.bf16 {%0,%1,%2,%3,%4,%5,%6,%7,%8,%9,%10,%11,%12,%13,%14,%15,%16,%17,%18,%19,%20,%21,%22,%23,%24,%25,%26,%27,%28,%29,%30,%31,%32,%33,%34,%35,%36,%37,%38,%39,%40,%41,%42,%43,%44,%45,%46,%47,%48,%49,%50,%51,%52,%53,%54,%55,%56,%57,%58,%59,%60,%61,%62,%63}, %64, %65, p, 1, 1, 0, 1;\n}\n"
                 : "+f"(acc[0]), "+f"(acc[1]), "+f"(acc[2]), "+f"(acc[3]), "+f"(acc[4]), "+f"(acc[5]), "+f"(acc[6]), "+f"(acc[7]), "+f"(acc[8]), "+f"(acc[9]), "+f"(acc[10]), "+f"(acc[11]), "+f"(acc[12]), "+f"(acc[13]), "+f"(acc[14]), "+f"(acc[15]), "+f"(acc[16]), "+f"(acc[17]), "+f"(acc[18]), "+f"(acc[19]), "+f"(acc[20]), "+f"(acc[21]), "+f"(acc[22]), "+f"(acc[23]), "+f"(acc[24]), "+f"(acc[25]), "+f"(acc[26]), "+f"(acc[27]), "+f"(acc[28]), "+f"(acc[29]), "+f"(acc[30]), "+f"(acc[31]), "+f"(acc[32]), "+f"(acc[33]), "+f"(acc[34]), "+f"(acc[35]), "+f"(acc[36]), "+f"(acc[37]), "+f"(acc[38]), "+f"(acc[39]), "+f"(acc[40]), "+f"(acc[41]), "+f"(acc[42]), "+f"(acc[43]), "+f"(acc[44]), "+f"(acc[45]), "+f"(acc[46]), "+f"(acc[47]), "+f"(acc[48]), "+f"(acc[49]), "+f"(acc[50]), "+f"(acc[51]), "+f"(acc[52]), "+f"(acc[53]), "+f"(acc[54]), "+f"(acc[55]), "+f"(acc[56]), "+f"(acc[57]), "+f"(acc[58]), "+f"(acc[59]), "+f"(acc[60]), "+f"(acc[61]), "+f"(acc[62]), "+f"(acc[63])
                 : "l"(da), "l"(db), "r"(sc));
}
__device__ __forceinline__ void wgmma_n40(float (&acc)[20], uint64_t da, uint64_t db, int sc) {
    asm volatile("{\n.reg .pred p;\nsetp.ne.b32 p, %22, 0;\nwgmma.mma_async.sync.aligned.m64n40k16.f32.bf16.bf16 {%0,%1,%2,%3,%4,%5,%6,%7,%8,%9,%10,%11,%12,%13,%14,%15,%16,%17,%18,%19}, %20, %21, p, 1, 1, 0, 1;\n}\n"
                 : "+f"(acc[0]), "+f"(acc[1]), "+f"(acc[2]), "+f"(acc[3]), "+f"(acc[4]), "+f"(acc[5]), "+f"(acc[6]), "+f"(acc[7]), "+f"(acc[8]), "+f"(acc[9]), "+f"(acc[10]), "+f"(acc[11]), "+f"(acc[12]), "+f"(acc[13]), "+f"(acc[14]), "+f"(acc[15]), "+f"(acc[16]), "+f"(acc[17]), "+f"(acc[18]), "+f"(acc[19])
                 : "l"(da), "l"(db), "r"(sc));
}
__device__ __forceinline__ void wgmma_n40_0(float (&acc)[20], uint64_t da, uint64_t db) {
    asm volatile("{\n.reg .pred p;\nsetp.ne.b32 p, 0, 0;\nwgmma.mma_async.sync.aligned.m64n40k16.f32.bf16.bf16 {%0,%1,%2,%3,%4,%5,%6,%7,%8,%9,%10,%11,%12,%13,%14,%15,%16,%17,%18,%19}, %20, %21, p, 1, 1, 0, 1;\n}\n"
                 : "=f"(acc[0]), "=f"(acc[1]), "=f"(acc[2]), "=f"(acc[3]), "=f"(acc[4]), "=f"(acc[5]), "=f"(acc[6]), "=f"(acc[7]), "=f"(acc[8]), "=f"(acc[9]), "=f"(acc[10]), "=f"(acc[11]), "=f"(acc[12]), "=f"(acc[13]), "=f"(acc[14]), "=f"(acc[15]), "=f"(acc[16]), "=f"(acc[17]), "=f"(acc[18]), "=f"(acc[19])
                 : "l"(da), "l"(db));
}
#define WG_N32(c, sc)                                                   \
    asm volatile(                                                       \
        "{\n"                                                           \
        ".reg .pred p;\n"           \
        "setp.ne.b32 p, " sc ", 0;\n"                                   \
        "wgmma.mma_async.sync.aligned.m64n32k16.f32.bf16.bf16 "         \
        "{%0,%1,%2,%3,%4,%5,%6,%7,%8,%9,%10,%11,%12,%13,%14,%15},"      \
        " {%16,%17,%18,%19}, %20, p, 1, 1, 0;\n"                        \
        "}\n"                                                           \
        : WG_ACC8(c, 0), WG_ACC8(c, 8)                                  \
        : "r"(a0), "r"(a1), "r"(a2), "r"(a3), "l"(db))
template <int SC>
__device__ __forceinline__ void wgmma_m64n32k16_rs(float (&acc)[16], uint32_t a0, uint32_t a1, uint32_t a2, uint32_t a3, uint64_t db) {
    if constexpr (SC == 1) WG_N32("+f", "1");
    else if constexpr (SC == 2) WG_N32("+f", "0");
    else WG_N32("=f", "0");
}

__host__ __device__ constexpr uint64_t make_desc(uint32_t addr, uint32_t lbo_bytes, uint32_t sbo_bytes, uint32_t swz) {
    uint64_t d = 0;
    d |= (uint64_t)((addr & 0x3FFFF) >> 4);
    d |= (uint64_t)((lbo_bytes >> 4) & 0x3FFF) << 16;
    d |= (uint64_t)((sbo_bytes >> 4) & 0x3FFF) << 32;
    d |= (uint64_t)swz << 62;
    return d;
}
__device__ __forceinline__ uint32_t ldg_u16(const __nv_bfloat16* p) { return (uint32_t)__ldg(reinterpret_cast<const unsigned short*>(p)); }
template <int N, class F, int... I>
__device__ __forceinline__ void static_for_impl(F&& f, std::integer_sequence<int, I...>) {
    (f(std::integral_constant<int, N + I>{}), ...);
}
template <int B, int E, class F>
__device__ __forceinline__ void static_for(F&& f) {
    static_for_impl<B>(f, std::make_integer_sequence<int, E - B>{});
}

__device__ __forceinline__ uint32_t hfma2_bf16(uint32_t a, uint32_t b, uint32_t c) {
    uint32_t r;
    asm("fma.rn.bf16x2 %0, %1, %2, %3;" : "=r"(r) : "r"(a), "r"(b), "r"(c));
    return r;
}
__device__ __forceinline__ float gelu2(float x) {
    const float k0 = 0.7978845608028654f, k01 = 0.7978845608028654f * 0.044715f;
    return fmaf(x, tanh_fast(x * fmaf(x * x, k01, k0)), x);
}
__device__ __forceinline__ uint32_t gelu2p(uint32_t x) {
    uint32_t t;
    const uint32_t u = hmul2_bf16(x, hfma2_bf16(hmul2_bf16(x, x), 0x3D123D12u, 0x3F4C3F4Cu));
    asm("tanh.approx.bf16x2 %0, %1;" : "=r"(t) : "r"(u));
    return hfma2_bf16(x, t, x);
}
__device__ __forceinline__ void wgmma_m64n8k16_rs(float (&acc)[4], const uint32_t* a, uint64_t db, int sc) {
    asm volatile("{\n.reg .pred p;\nsetp.ne.b32 p, %9, 0;\nwgmma.mma_async.sync.aligned.m64n8k16.f32.bf16.bf16 {%0,%1,%2,%3}, {%4,%5,%6,%7}, %8, p, 1, 1, 0;\n}\n"
                 : "+f"(acc[0]), "+f"(acc[1]), "+f"(acc[2]), "+f"(acc[3])
                 : "r"(a[0]), "r"(a[1]), "r"(a[2]), "r"(a[3]), "l"(db), "r"(sc));
}

template <int SC>
__device__ __forceinline__ void wgmma_m64n16k16_rs(float (&acc)[8], const uint32_t* a, uint64_t db) {
    asm volatile("{\n.reg .pred p;\nsetp.ne.b32 p, %13, 0;\nwgmma.mma_async.sync.aligned.m64n16k16.f32.bf16.bf16 {%0,%1,%2,%3,%4,%5,%6,%7}, {%8,%9,%10,%11}, %12, p, 1, 1, 0;\n}\n"
                 : WG_ACC8("+f", 0)
                 : "r"(a[0]), "r"(a[1]), "r"(a[2]), "r"(a[3]), "l"(db), "n"(SC));
}

constexpr int SB0 = 1024;
constexpr int SLOT = 4096;
constexpr int EWP = SLOT + 16;
constexpr int OFF_EW = 608;
constexpr int OFF_RT = 1024;
constexpr int RT = 8192;
__host__ __device__ constexpr int tile(int f) { return f == 13 ? 17 : f < 21 ? (f + 11 * (f & 1)) / 2 : (f & 1) ? (f + 1) / 2 : f - 5; }
__host__ __device__ constexpr int w1_dist(int f) { return f < 16 ? (int)(0x5713457134571345ull >> (4 * f)) & 7 : (0x5134 >> (4 * (f & 3))) & 7; }
constexpr int HS_BYTES = 16384;
constexpr int OFF_WBI = OFF_RT + 26 * RT;
constexpr int OFF_IDX = OFF_RT + 15 * RT;
constexpr int OFF_SEF = OFF_WBI + RT;
constexpr int OFF_AP = OFF_SEF + 2048;
constexpr int OFF_W2 = 0;
constexpr int OFF_DP = OFF_AP + 4096;
constexpr int OFF_ID = OFF_DP + 6 * 32 * 4;
constexpr int OFF_BAR = OFF_ID + 256;
constexpr int TILE = 2048;
constexpr int CHUNK = 4 * TILE;
constexpr int NCHUNK = 16;
constexpr uint64_t CPOS = 0x21A70D986543CB21ull;
static_assert(OFF_EW + 25 * EWP + SLOT <= OFF_RT + 13 * RT && CHUNK == RT, "layout");
static_assert(OFF_ID % 128 == 0, "align");
constexpr int B_CFULL = 0,
              B_F = 4,
              B_W = 16,
              B_EMPTY = 48, B_ZRDY = B_EMPTY + NF, B_CDONE = B_ZRDY + 1,
              B_EWRDY = B_CDONE + 2, B_PAIR = 80,
              B_IDX = B_PAIR + 13, B_FIN = B_PAIR + 14;
constexpr int OFF_TS = OFF_BAR + 768;
constexpr int SMEM = OFF_TS + 512;
static_assert(SMEM <= 232448, "smem");
constexpr int NFIRST = 4;
constexpr int NP = 2;
constexpr int NUNIT = 128;

__device__ __align__(1024) uint8_t g_wt[2 * NCHUNK * CHUNK];
__device__ unsigned int g_cnt;

__device__ __forceinline__ void u_lda(uint32_t (&A)[8], uint32_t a0, uint32_t a1) {
    ldsm_x4_t(a0, A[0], A[1], A[2], A[3]);
    ldsm_x4_t(a1, A[4], A[5], A[6], A[7]);
}
__device__ __forceinline__ void u_mma(float (&acc)[16], const uint32_t (&A)[8], uint64_t desc) {
    wgmma_m64n32k16_rs<2>(acc, A[0], A[1], A[2], A[3], desc);
    wgmma_m64n32k16_rs<1>(acc, A[4], A[5], A[6], A[7], desc + 64);
}
__device__ __forceinline__ void send_addr(uint32_t sb, int src, int w4, uint32_t& da, uint32_t& db, uint32_t& t) {
    uint32_t rb, l;
    asm volatile("mov.u32 %0, %%laneid;" : "=r"(l));
    asm volatile("mapa.shared::cluster.u32 %0, %1, %2;" : "=r"(rb) : "r"(sb), "r"(w4 >> 1));
    da = opq(rb + OFF_DP + (src * 32 + (w4 & 1) * 16 + 8 * (l & 1) + (l >> 2)) * 4);
    db = opq(rb + OFF_BAR + B_FIN * 8 + (l >> 5));
    t = l & 3;
}
__device__ __forceinline__ void send_partial(uint32_t da, uint32_t db, uint32_t t, float v0, float v1) {
    asm volatile("{\n.reg .pred p;\nsetp.lt.u32 p, %3, 2;\n@p st.async.weak.shared::cluster.mbarrier::complete_tx::bytes.f32 [%0], %1, [%2];\n}\n" ::"r"(da), "f"(t ? v1 : v0),
                 "r"(db), "r"(t)
                 : "memory");
}

__global__ void __cluster_dims__(2, 1, 1) __launch_bounds__(512, 1)
fused_kernel(const int* __restrict__ idx, const __nv_bfloat16* __restrict__ table, const __nv_bfloat16* __restrict__ w1, const __nv_bfloat16* __restrict__ w_bi,
             const __nv_bfloat16* __restrict__ w2, const __nv_bfloat16* __restrict__ w_cross, const __nv_bfloat16* __restrict__ se_w1,
             const __nv_bfloat16* __restrict__ se_w2, __nv_bfloat16* __restrict__ out, const __grid_constant__ CUtensorMap tmW1) {
    extern __shared__ __align__(1024) uint8_t smem_raw[];
    const int tid = threadIdx.x, b = (tid >> 3) & 31;
    const int pb0 = (blockIdx.x >> 1) * 64;
    int2 i0a, i0b, i1a, i1b;
    asm volatile("ld.global.nc.v2.u32 {%0,%1}, [%8];\nld.global.nc.v2.u32 {%2,%3}, [%8 + 3328];\nld.global.nc.v2.u32 {%4,%5}, [%8 + 8];\nld.global.nc.v2.u32 {%6,%7}, [%8 + 3336];"
                 : "=r"(i0a.x), "=r"(i0a.y), "=r"(i0b.x), "=r"(i0b.y), "=r"(i1a.x), "=r"(i1a.y), "=r"(i1b.x), "=r"(i1b.y)
                 : "l"(idx + (pb0 + b) * NF));
    const uint32_t sb = __shfl_sync(0xffffffffu, smem_u32(smem_raw), 0);
    const uint32_t bars = sb + OFF_BAR;
#define BAR(i) (bars + (i) * 8)
    const int warp = __shfl_sync(0xffffffffu, tid >> 5, 0), lane = tid & 31, g = lane >> 2, t = lane & 3;
    const int rank = blockIdx.x & 1;
    if (tid == 0) TS(0);
    if (elect_one()) {
        mbar_init(BAR(B_PAIR + warp), warp < 13 ? 256 + (warp == 10) : 1);
        if (warp >= 13) {
            asm volatile("fence.mbarrier_init.release.cluster;" ::: "memory");
            mbar_expect_tx(BAR(B_PAIR + warp), warp == 13 ? 64 * NF * 4 : 6 * 32 * 4);
            if (warp == 13) bulk_load(sb + OFF_IDX, idx + pb0 * NF, 64 * NF * 4, BAR(B_IDX));
        }
        if (warp == 6) asm volatile("cp.async.bulk.prefetch.L2.global [%0], %1;" ::"l"((const char*)w1 + 19 * 32768 + blockIdx.x * 1792), "n"(1792) : "memory");
        mbar_init(BAR(16 + warp), (warp & 1) || !warp ? 1 : 9);
        mbar_init(BAR(32 + warp), (warp & 1) && warp != 9 ? 1 : 9);
        mbar_init(BAR(48 + warp), 4);
        mbar_init(BAR(64 + warp), warp == B_CDONE - 64 ? 8 : 4);
        if (warp < 4 + NP) mbar_init(BAR(warp), warp < 4 ? (0x3421 >> (4 * warp)) & 7 : 256);
        asm volatile("fence.mbarrier_init.release.cluster;" ::: "memory");
    }
    __syncthreads();
    asm volatile("barrier.cluster.arrive.relaxed.aligned;" ::: "memory");
    if (tid == 0) TS(1);

    if (warp >= 12) {
        asm volatile("setmaxnreg.dec.sync.aligned.u32 %0;" ::"n"(R_PROD));
        if ((sb & 0xFFFFFFu) != SB0) __trap();
        if (warp == 12) {
            const uint32_t c0 = clock();
#pragma unroll 1
            for (int f = 0; f < NF; f++) {
                const uint32_t dist = w1_dist(f) * RT;
                if (f >= 5) mbar_wait_bounded(BAR(B_EMPTY + f - (f < 19 ? 5 : 4)), 0);
                while (f < 5 && (uint32_t)clock() - c0 < f * 450) __nanosleep(32);
                TSL(80 + f);
                if (elect_one()) {
                    mbar_expect_tx(BAR(B_W + f), HS_BYTES);
                    tma_load_3d(sb + OFF_WBI - 2 * dist, &tmW1, 0, f * 64, rank * 2, BAR(B_W + f));
                    tma_load_3d(sb + OFF_WBI - dist, &tmW1, 0, f * 64, rank * 2 + 1, BAR(B_W + f));
                }
            }
            asm volatile("barrier.cluster.wait.acquire.aligned;" ::: "memory");
            const uint64_t po = (uint64_t)(out + pb0 + 32 * rank + lane);
            const uint32_t plo = opq((uint32_t)po), phi = opq((uint32_t)(po >> 32) + (lane >> 5)), dp = opq(sb + OFF_DP + lane * 4);
            mbar_wait_bounded(BAR(B_FIN), 0);
            const uint4 u = make_uint4(lds32(dp), lds32(dp + 128), lds32(dp + 256), lds32(dp + 384));
            const uint2 v = make_uint2(lds32(dp + 512), lds32(dp + 640));
            asm volatile("st.global.u16 [%0], %1;" ::"l"(((uint64_t)phi << 32) | plo),
                         "h"(__bfloat16_as_ushort(__float2bfloat16_rn((__uint_as_float(u.x) + __uint_as_float(u.y)) + (__uint_as_float(u.z) + __uint_as_float(u.w)) +
                                                                      (__uint_as_float(v.x) + __uint_as_float(v.y)))))
                         : "memory");
            TSL(15);
        } else {
            if (warp == 13) {
                const uint32_t sr = sb + OFF_AP;
                {
                    uint32_t v[12];
#pragma unroll
                    for (int i = 0; i < 12; i++) v[i] = lane + 32 * (i >> 1) < NF * NFR / 2 ? __ldg(reinterpret_cast<const uint32_t*>((i & 1) ? se_w2 : se_w1) + lane + 32 * (i >> 1)) : 0u;
#pragma unroll
                    for (int i = 0; i < 12; i++) asm volatile("st.shared.u32 [%0], %1;" ::"r"(sr + lane * 4 + (i >> 1) * 128 + (i & 1) * 1024), "r"(v[i]) : "memory");
                    __syncwarp();
                }
#pragma unroll 1
                for (int q = 0; q < 8; q++) {
                    const int c1 = 8 * (q & 1) + g, o1 = c1 < NFR ? min((8 * (q >> 1) + 2 * t) * NFR + c1, NF * NFR) : NF * NFR;
                    const int c2 = 8 * (q & 3) + ((q & 3) < 3 ? 4 * (g & 1) + (g >> 1) : (g & 1)), o2 = min((8 * (q >> 2) + 2 * t) * NF + c2, NF * NFR);
                    uint32_t y1, y2;
                    asm volatile("{\n.reg .b16 a, b, c, d;\nld.shared.b16 a, [%2];\nld.shared.b16 b, [%2 + 26];\nld.shared.b16 c, [%3 + 1024];\nld.shared.b16 d, [%3 + 1076];\n"
                                 "mov.b32 %0, {a, b};\nmov.b32 %1, {c, d};\n}\n" : "=r"(y1), "=r"(y2) : "r"(sr + 2 * o1), "r"(sr + 2 * o2));
                    asm volatile("st.shared.u32 [%0], %1;\nst.shared.u32 [%0 + 1024], %2;" ::"r"(sb + OFF_SEF + q * 128 + lane * 4), "r"(y1),
                                 "r"(hmul2_bf16(y2, 0x3E803E80u))
                                 : "memory");
                }
                fence_proxy_async();
                __syncwarp();
                TSL(12);
                if (elect_one()) mbar_arrive(BAR(B_PAIR + 10));
            } else if (warp == 15) {
                {
                    const int pq = blockIdx.x >> 6, js = (blockIdx.x >> 1) & 31;
                    const int j = js < 24 ? (js & 24) + 4 * (js & 1) + ((js >> 1) & 3) : 24 + (js & 1);
                    const bool on = js < 24 || ((js >> 1) & 3) == ((lane >> 2) & 3);
                    const __nv_bfloat16* s = w_cross + ((size_t)(pq * NF) * NF + j) * ND + 32 * rank + lane;
                    uint8_t* d = g_wt + (size_t)rank * NCHUNK * CHUNK + (((lane & 15) >> 1) * 2 + (lane >> 4)) * CHUNK + ((lane & 1) * 2 + pq) * TILE + js * 16;
#pragma unroll 1
                    for (int kh = 0; kh < 2; kh++) {
                        uint32_t x[8];
#pragma unroll
                        for (int k = 0; k < 8; k++)
                            x[k] = (on && (kh == 0 || k < 5)) ? ldg_u16(s + (k + (k & 4)) * NF * ND) | (ldg_u16(s + (k == 4 && kh ? 9 : k + (k & 4) + 4) * NF * ND) << 16) : 0u;
                        *reinterpret_cast<uint4*>(d) = make_uint4(x[0], x[1], x[2], x[3]);
                        *reinterpret_cast<uint4*>(d + 512) = make_uint4(x[4], x[5], x[6], x[7]);
                        s += 16 * NF * ND;
                        d += 1024;
                    }
                    __syncwarp();
                }
                TSL(8);
                if (elect_one()) asm volatile("red.release.gpu.global.inc.u32 [%0], %1;" ::"l"(&g_cnt), "n"(NUNIT + 127) : "memory");
                TSL(9);
                mbar_wait(BAR(B_EMPTY + 6), 0);
                TSL(10);
                unsigned int v;
                do {
                    asm volatile("ld.acquire.gpu.global.u32 %0, [%1];" : "=r"(v) : "l"(&g_cnt) : "memory");
                } while (v < NUNIT);
                asm volatile("fence.proxy.async.global;" ::: "memory");
                __syncwarp();
                if (elect_one()) asm volatile("red.relaxed.gpu.global.inc.u32 [%0], %1;" ::"l"(&g_cnt), "n"(NUNIT + 127) : "memory");
                TSL(11);
                const uint8_t* wsrc = g_wt + (size_t)rank * NCHUNK * CHUNK;
                static_for<0, 10>([&](auto KC) {
                    constexpr int k = decltype(KC)::value, T[10][4] = {{0, 2, 5, 0}, {10, 1, 12, 2}, {2, 2, 8, 1}, {4, 2, 9, 1}, {6, 2, 10, 2}, {8, 2, 10, 2}, {11, 1, 11, 2}, {12, 1, 11, 3}, {13, 1, 11, 3}, {14, 2, 13, 3}};
                    if (k == 0 || T[k][2] != T[k ? k - 1 : 0][2]) mbar_wait(BAR(B_EMPTY + 14 + T[k][2]), 0);
                    TSL(30 + k);
                    if (elect_one()) {
                        mbar_expect_tx(BAR(B_CFULL + T[k][3]), T[k][1] * CHUNK);
                        bulk_load(sb + OFF_RT + (13 + ((int)(CPOS >> (4 * T[k][0])) & 15)) * RT, wsrc + T[k][0] * CHUNK, T[k][1] * CHUNK, BAR(B_CFULL + T[k][3]));
                    }
                });
            }
            __syncwarp();
            asm volatile("barrier.cluster.wait.acquire.aligned;" ::: "memory");
        }
    } else if (warp < 4) {
        {
            const uint4* wb = reinterpret_cast<const uint4*>(w_bi + (tid >> 2) * 64 + 32 * rank + 8 * t);
            const uint4 wb0 = __ldg(wb), wb1 = __ldg(wb + 256);
            const uint32_t w2v = __ldg(reinterpret_cast<const uint32_t*>(w2) + rank * 64 + (tid & 63));
            sts128(sb + OFF_WBI + (tid & 63) * 128 + ((4 ^ (tid & 7)) << 4), 0x3C803C80u, 0x3C803C80u, 0x3C803C80u, 0x3C803C80u);
            asm volatile("st.shared.u32 [%0], %1;" ::"r"(sb + OFF_ID + (tid & 63) * 4), "r"(0x3F803F80u) : "memory");
            asm volatile("st.shared.u32 [%0], %1;" ::"r"(sb + OFF_W2 + (tid & 56) * 4 + (tid & 3) * 8 + (tid & 4)), "r"(w2v) : "memory");
            const uint32_t wd = sb + OFF_WBI + (tid >> 2) * 128 + ((t ^ (g & 7)) << 4);
            sts128(wd, wb0.x, wb0.y, wb0.z, wb0.w);
            sts128(wd + 4096, wb1.x, wb1.y, wb1.z, wb1.w);
            fence_proxy_async();
        }
        asm volatile("setmaxnreg.inc.sync.aligned.u32 %0;" ::"n"(R_DEEP));
        asm volatile("bar.sync 1, 128;" ::: "memory");
        asm volatile("barrier.cluster.wait.acquire.aligned;" ::: "memory");
        TS(7);
        float acc[2][84], e2[2][20], ad[64];
#pragma unroll
        for (int i = 0; i < 84; i++) asm volatile("" : "=f"(acc[0][i]), "=f"(acc[1][i]));
        const uint32_t sa = opq(sb + OFF_EW + (lane >> 4) * 128 + (2 * warp + ((lane >> 3) & 1)) * 512 + (lane & 7) * 16);
        const uint32_t ln = opq(lane);
        const bool l0 = ln == 0;
        uint32_t za[8];
#pragma unroll
        for (int i = 0; i < 6; i++) asm volatile("" : "=r"(za[i]));
        auto cvt = [&](uint32_t (&pk)[8], int f) {
            const float* e = f < 22 ? acc[f & 1] + 64 : e2[f & 1];
#pragma unroll
            for (int i = 0; i < 8; i++) asm volatile("cvt.rn.bf16x2.f32 %0, %1, %2;" : "=r"(pk[i]) : "f"(e[2 * i + 1]), "f"(e[2 * i]));
            uint32_t &z0 = za[2 * (f >> 3)], &z1 = za[2 * (f >> 3) + 1];
            asm volatile("{\n.reg .pred p;\nsetp.eq.u32 p, %6, %7;\n@p cvt.rn.bf16x2.f32 %0, %2, %4;\n@p cvt.rn.bf16x2.f32 %1, %3, %5;\n}\n"
                         : "+r"(z0), "+r"(z1)
                         : "f"(e[16]), "f"(e[18]), "f"((f & 1) ? __uint_as_float(z0) : 0.f), "f"((f & 1) ? __uint_as_float(z1) : 0.f), "r"(ln & 3), "r"((f >> 1) & 3));
        };
        auto store = [&](const uint32_t (&pk)[8], int f) {
            stsm_x4_t(sa + f * EWP, pk[0], pk[1], pk[2], pk[3]);
            stsm_x4_t(sa + f * EWP + 256, pk[4], pk[5], pk[6], pk[7]);
        };
        auto da = [](int f, int i) { return make_desc(SB0 + OFF_RT + tile(f) * RT, 16, 1024, 1) + 2 * (i ^ (2 * (f & 1))); };
        auto db = [](int f, int i) { return make_desc(SB0 + OFF_WBI - 2 * w1_dist(f) * RT, w1_dist(f) * RT, 1024, 1) + 128 * i; };
        auto mma_e = [&](int f) {
            wgmma_fence();
#pragma unroll
            for (int i = 0; i < 4; i++) {
                if (i) wgmma_n40(e2[f & 1], da(f, i), make_desc(SB0 + OFF_WBI, RT, 1024, 1) + 128 * i, 1);
                else wgmma_n40_0(e2[f & 1], da(f, i), make_desc(SB0 + OFF_WBI, RT, 1024, 1));
            }
            wgmma_commit();
        };
        auto mma_d = [&](int f, int i0, int i1) {
#pragma unroll
            for (int i = i0; i < i1; i++) wgmma_n128(ad, da(f, i), db(f, i), 1);
            wgmma_commit();
        };
#define ROWS_TO_ASYNC() asm volatile("fence.proxy.async::generic.acquire.sync_restrict::shared::cluster.cluster;" ::: "memory")
#define SYNC4() asm volatile("bar.sync 1, 128;" ::: "memory")
        uint32_t pk[8];
        static_for<0, 22>([&](auto KC) {
            constexpr int k = decltype(KC)::value;
            if (k > 1) {
                wgmma_wait<1>();
                if (l0) mbar_arrive(BAR(B_EMPTY + k - 2));
                cvt(pk, k - 2);
#pragma unroll
                for (int i = 64; i < 83; i++)
                    if (i != 81) asm volatile("mul.f32 %0, %0, 0f00000000;" : "+f"(acc[k & 1][i]));
            }
            if (k < 2 * NP || !(k & 1)) mbar_wait(BAR((k < 2 * NP && !(k & 1) ? B_F : B_PAIR) + k / 2), 0);
            mbar_wait(BAR(B_W + k), 0);
            ROWS_TO_ASYNC();
            if (k == 0) TS(19);
            wgmma_fence();
#pragma unroll
            for (int i = 0; i < 4; i++) wgmma_n168(acc[k & 1], da(k, i), db(k, i), k > 1 || i);
            wgmma_commit();
            if (k > 1) {
                SYNC4();
                store(pk, k - 2);
            }
        });
        {
            uint32_t p2[8], p3[8], p4[8];
            wgmma_wait<1>();
            if (l0) mbar_arrive(BAR(B_EMPTY + 20));
            cvt(pk, 20);
            mbar_wait(BAR(B_PAIR + 11), 0);
            mbar_wait(BAR(B_PAIR + 12), 0);
            mbar_wait(BAR(B_W + 22), 0);
            ROWS_TO_ASYNC();
            mma_e(22);
            SYNC4();
            store(pk, 20);
            wgmma_wait<1>();
            if (l0) mbar_arrive(BAR(B_EMPTY + 21));
            cvt(pk, 21);
#pragma unroll
            for (int i = 0; i < 64; i++) asm volatile("add.f32 %0, %1, %2;" : "=f"(ad[i]) : "f"(acc[0][i]), "f"(acc[1][i]));
            wgmma_fence();
            mma_d(22, 0, 1);
            mma_e(23);
            store(pk, 21);
            wgmma_wait<2>();
            cvt(p2, 22);
            mma_e(24);
            SYNC4();
            store(p2, 22);
            wgmma_wait<1>();
            cvt(p3, 23);
            mma_e(25);
            mma_d(22, 1, 3);
            store(p3, 23);
            wgmma_wait<1>();
            if (l0) mbar_arrive(BAR(B_ZRDY));
            TS(2);
            za[6] = za[7] = 0u;
            cvt(pk, 24);
            cvt(p4, 25);
#pragma unroll
            for (int i = 0; i < 6; i++) za[i] |= p4[7] & (ln >> 5);
            constexpr uint64_t d1 = make_desc(SB0 + OFF_SEF, 256, 128, 0), d2 = make_desc(SB0 + OFF_SEF + 1024, 512, 128, 0);
            float h[8], o[16];
#pragma unroll
            for (int i = 0; i < 16; i++) asm volatile("" : "=f"(o[i]), "=f"(h[i & 7]));
            wgmma_fence();
            wgmma_m64n16k16_rs<0>(h, za, d1);
            wgmma_m64n16k16_rs<1>(h, za + 4, d1 + 32);
            wgmma_commit();
            mma_d(22, 3, 4);
            mbar_wait(BAR(B_W + 23), 0);
            wgmma_fence();
            mma_d(23, 0, 4);
            wgmma_wait<2>();
            const uint32_t ha0 = pack_bf16(gelu2(h[0]), gelu2(h[1])), ha1 = pack_bf16(gelu2(h[2]), gelu2(h[3])), ha2 = pack_bf16(gelu2(h[4]), gelu2(h[5])),
                           ha3 = pack_bf16(gelu2(h[6]), gelu2(h[7]));
            wgmma_fence();
            wgmma_m64n32k16_rs<2>(o, ha0, ha1, ha2, ha3, d2);
            wgmma_commit();
            wgmma_wait<2>();
            if (l0) mbar_arrive(BAR(B_EMPTY + 22));
            mbar_wait(BAR(B_W + 24), 0);
            wgmma_fence();
            mma_d(24, 0, 4);
            wgmma_wait<1>();
            if (l0) mbar_arrive(BAR(B_EMPTY + 23));
            mbar_wait(BAR(B_W + 25), 0);
            wgmma_fence();
            mma_d(25, 0, 4);
            SYNC4();
            store(pk, 24);
            store(p4, 25);
#pragma unroll
            for (int i = 0; i < 2; i++) {
                uint32_t a[4];
#pragma unroll
                for (int k = 0; k < 4; k++) a[k] = pack_bf16(fmaf(tanh_fast(o[8 * i + 2 * k]), 0.5f, 0.5f), fmaf(tanh_fast(o[8 * i + 2 * k + 1]), 0.5f, 0.5f));
                sts128(sb + OFF_AP + i * 2048 + warp * 512 + ln * 16, a[0], a[1], a[2], a[3]);
            }
            __syncwarp();
            if (l0) mbar_arrive(BAR(B_EWRDY));
            wgmma_wait<1>();
            if (l0) mbar_arrive(BAR(B_EMPTY + 24));
            TS(3);
        }
        {
            wgmma_wait<0>();
            if (l0) mbar_arrive(BAR(B_EMPTY + 25));
            uint32_t hw[32];
#pragma unroll
            for (int i = 0; i < 32; i++) asm volatile("cvt.rn.bf16x2.f32 %0, %1, %2;" : "=r"(hw[i]) : "f"(ad[2 * i + 1]), "f"(ad[2 * i]));
            asm volatile("setmaxnreg.dec.sync.aligned.u32 %0;" ::"n"(R_DEEP2));
            TS(4);
            float o[4] = {0.f, 0.f, 0.f, 0.f};
            int l2;
            asm volatile("mov.u32 %0, %%laneid;" : "=r"(l2));
#pragma unroll
            for (int it = 0; it < 8; it++) {
                uint32_t b0, b1;
                asm volatile("ld.shared.v2.u32 {%0,%1}, [%2];" : "=r"(b0), "=r"(b1) : "r"(sb + OFF_W2 + 8 * (l2 & 3) + it * 32));
                mma16816(o, gelu2p(hw[4 * it]), gelu2p(hw[4 * it + 1]), gelu2p(hw[4 * it + 2]), gelu2p(hw[4 * it + 3]), b0, b1);
            }
            uint32_t da, db, tt;
            send_addr(sb, rank * 3, warp, da, db, tt);
            send_partial(da, db, tt, 0.5f * o[0], 0.5f * o[2]);
        }
        TS(5);
    } else {
        const int wgc = (warp >> 2) - 1, w4 = warp & 3;
        const char* so = (const char*)table + 16 * (lane & 7);
        auto rp = [&](uint32_t i) { return row_ptr(so, i); };
        const uint32_t d0 = opq(sb + OFF_RT + b * 128 + (((lane ^ b) & 7) << 4)), d1 = opq((d0 ^ 64) + 6 * RT);
        uint32_t c0;
        auto until = [&](int f) {
            for (;;) {
                uint32_t c;
                asm volatile("mov.u32 %0, %%clock;" : "=r"(c)::"memory");
                if (c - c0 >= f * 300) break;
                __nanosleep(32);
            }
        };
        {
            const int ia[4] = {i0a.x, i0a.y, i1a.x, i1a.y}, ib[4] = {i0b.x, i0b.y, i1b.x, i1b.y};
            static_for<0, NFIRST>([&](auto FC) {
                constexpr int f = decltype(FC)::value, o = (f >> 1) * RT;
                if (f) until(f);
                cp_async16(((f & 1) ? d1 : d0) + o, rp(ia[f]));
                cp_async16(((f & 1) ? d1 : d0) + o + 4096, rp(ib[f]));
                cp_async_mbar_arrive_noinc(BAR(((f & 1) ? B_PAIR : B_F) + (f >> 1)));
                if (f == 0) asm volatile("mov.u32 %0, %%clock;" : "=r"(c0)::"memory");
            });
            if (wgc == 0) TS(6);
        }
        asm volatile("setmaxnreg.inc.sync.aligned.u32 %0;" ::"n"(R_CR1));
        uint32_t M[8][12], y[4][2];
        {
            const uint32_t pa = opq(sb + OFF_RT + (t & 1) * 6 * RT + (16 * w4 + g) * 128 + (((4 * rank + 2 * wgc) ^ g ^ (4 * (t & 1))) << 4)), t1 = opq(t >> 1);
            const uint32_t ia = opq(sb + OFF_IDX + b * NF * 4);
#pragma unroll
            for (int i = 0; i < 96; i++) asm volatile("" : "=r"(M[i / 12][i % 12]));
            mbar_wait(BAR(B_IDX), 0);
            uint32_t x[13][4];
#pragma unroll
            for (int p = 2; p < 13; p++)
                asm volatile("ld.shared.v2.u32 {%0,%1}, [%4];\nld.shared.v2.u32 {%2,%3}, [%4 + 3328];" : "=r"(x[p][0]), "=r"(x[p][2]), "=r"(x[p][1]), "=r"(x[p][3]) : "r"(ia + p * 8));
            const uint32_t pb = opq(pa ^ 16);
            auto conv = [&](int G) {
#pragma unroll
                for (int i = 0; i < 16; i++) {
                    uint32_t &u = M[i >> 1][4 * G + 2 * (i & 1)], &v = M[i >> 1][4 * G + 2 * (i & 1) + 1];
                    asm volatile("{\n.reg .b32 t;\nprmt.b32 t, %0, %1, 0x5410;\nprmt.b32 %1, %0, %1, 0x7632;\nmov.b32 %0, t;\n}\n" : "+r"(u), "+r"(v));
                }
#pragma unroll
                for (int i = 0; i < 8; i++)
                    asm volatile("{\n.reg .pred p;\nsetp.eq.u32 p, %5, 2;\n@p st.shared.v4.u32 [%4], {%0,%1,%2,%3};\n}\n" ::"r"(M[i & 4][4 * G + (i & 3)]), "r"(M[(i & 4) + 1][4 * G + (i & 3)]),
                                 "r"(M[(i & 4) + 2][4 * G + (i & 3)]), "r"(M[(i & 4) + 3][4 * G + (i & 3)]), "r"(pa), "r"(t1));
            };
            auto gather = [&](auto PC) {
                constexpr int p = decltype(PC)::value;
                constexpr uint32_t o1 = (tile(2 * p + 1) - 6) * RT;
                if (p < 6) until(2 * p);
                cp_async16(d0 + tile(2 * p) * RT, rp(x[p][0]));
                cp_async16(d0 + tile(2 * p) * RT + 4096, rp(x[p][1]));
                if (p < NP) cp_async_mbar_arrive_noinc(BAR(B_F + p));
                if (p < 6) until(2 * p + 1);
                cp_async16(d1 + o1, rp(x[p][2]));
                cp_async16(d1 + o1 + 4096, rp(x[p][3]));
                cp_async_mbar_arrive_noinc(BAR(B_PAIR + p));
            };
            auto pick = [&](auto QC) {
                constexpr int q = decltype(QC)::value, c = 4 * (q >> 2) + ((q >> 1) & 1);
#pragma unroll
                for (int i = 0; i < 4; i++)
                    asm volatile("{\n.reg .pred p;\nsetp.eq.u32 p, %5, %6;\n@p ld.shared.v4.u32 {%0,%1,%2,%3}, [%4];\n}\n"
                                 : "+r"(M[2 * (i & 2)][c + 2 * (i & 1)]), "+r"(M[2 * (i & 2) + 1][c + 2 * (i & 1)]), "+r"(M[2 * (i & 2) + 2][c + 2 * (i & 1)]),
                                   "+r"(M[2 * (i & 2) + 3][c + 2 * (i & 1)])
                                 : "r"(((i & 2) ? pb : pa) + tile(2 * q) * RT + (i & 1) * 1024 + (tile(2 * q + 1) - 6 - tile(2 * q)) * (t & 1) * RT), "r"(t1), "n"(q & 1));
                __syncwarp();
                if (elect_one()) mbar_arrive(BAR(B_W + 2 * q + 2));
                if (q == 4 || q == 8) conv(q / 4 - 1);
            };
#define IC(x) std::integral_constant<int, x>{}
            gather(IC(2));
            gather(IC(3));
            static_for<0, 3>([&](auto QC) {
                constexpr int q = decltype(QC)::value;
                mbar_wait(BAR(B_PAIR + q), 0);
                pick(QC);
                if constexpr (q < 2) gather(IC(q + 4));
            });
            static_for<3, 12>([&](auto QC) {
                constexpr int q = decltype(QC)::value, p = q < 7 ? q + 3 : q == 8 ? 10 : q == 11 ? 12 : 0;
                if (q == 10) {
                    mbar_wait(BAR(B_EMPTY + 14), 0);
                    gather(IC(11));
                }
                mbar_wait(BAR(B_EMPTY + 2 * q - 5 - (q == 11)), 0);
                if constexpr (p == 12) gather(IC(12));
                mbar_wait(BAR(B_PAIR + q), 0);
                if constexpr (p && p < 12) gather(IC(p));
                if (q == 9) {
#pragma unroll
                    for (int i = 0; i < 4; i++) asm volatile("prefetch.global.L2 [%0];" ::"l"(rp(rank ? x[11 + (i >> 1)][2 * (i & 1) + 1] : x[11 + (i >> 1)][2 * (i & 1)])));
                }
                pick(QC);
            });
            const uint32_t ta = sb + OFF_RT + tile(24) * RT + (16 * w4 + g) * 128 + (((4 * rank + 2 * wgc + (t >> 1)) ^ g) << 4) + 8 * (t & 1);
            mbar_wait(BAR(B_PAIR + 12), 0);
#pragma unroll
            for (int k = 0; k < 4; k++) asm volatile("ld.shared.v2.u32 {%0,%1}, [%2];" : "=r"(y[k][0]), "=r"(y[k][1]) : "r"(((k & 1) ? (ta ^ 64) - (tile(24) - tile(25)) * RT : ta) + (k >> 1) * 1024));
            __syncwarp();
            if (elect_one()) mbar_arrive(BAR(B_W + 25));
            conv(2);
        }
        uint32_t TL[4][2];
        uint32_t ap[8], a0, a1;
        uint32_t A0[8], A1[8], Aq[8], w[8], aq;
        {
            const int r = lane & 7, bh = (lane >> 3) & 1, ig = lane >> 4;
            const uint32_t x = sb + OFF_EW + wgc * 256 + (2 * w4 + bh) * 512 + (8 * ig + 4 * (r & 1) + (r >> 1)) * EWP;
            a0 = opq(x);
            a1 = opq(x + (!ig || r == 0 ? 16 : r == 1 ? 13 : r == 2 ? 11 : 8) * EWP);
            aq = opq(sb + OFF_AP + w4 * 512 + lane * 16);
        }
        asm volatile("barrier.cluster.wait.acquire.aligned;" ::: "memory");
        mbar_wait(BAR(B_CFULL), 0);
        mbar_wait(BAR(B_EWRDY), 0);
        u_lda(A0, a0, a1);
#pragma unroll
        for (int i = 0; i < 2; i++) {
            const uint4 v = lds128(aq + i * 2048);
            ap[4 * i] = v.x, ap[4 * i + 1] = v.y, ap[4 * i + 2] = v.z, ap[4 * i + 3] = v.w;
        }
        if (wgc == 0) TS(60);
        asm volatile("setmaxnreg.inc.sync.aligned.u32 %0;" ::"n"(R_CR2));
        if (wgc == 0) TS(61);
        asm volatile("mov.u32 %0, %%clock;\nand.b32 %0, %0, %1;" : "=r"(aq) : "r"(warp >> 4));
        a0 |= aq, a1 |= aq;
#pragma unroll
        for (int k = 0; k < 8; k++) {
            TL[k >> 1][k & 1] = __byte_perm(y[2 * (k & 1)][k >> 2], y[2 * (k & 1) + 1][k >> 2], (0x5410 + 0x2222 * ((k >> 1) & 1)) | aq);
            ap[k] |= aq, A0[k] |= aq & TL[k >> 1][k & 1];
        }
        constexpr uint64_t dt = make_desc(SB0 + OFF_RT + 13 * RT, 512, 128, 0), dqc = make_desc(SB0 + OFF_ID, 128, 128, 0);
        const uint64_t dq = uni64(dqc + (sb >> 28));
        auto dsc = [&](int e, int pq) {
            const int s0 = (int)(CPOS >> (8 * (e >> 1))) & 15, s1 = (int)(CPOS >> (8 * (e >> 1) + 4)) & 15;
            return dt + (s0 + wgc * (s1 - s0)) * (CHUNK >> 4) + ((e & 1) * 2 + pq) * (TILE >> 4);
        };
        float S[4], accP[16], accQ[16];
#pragma unroll
        for (int i = 0; i < 16; i++) asm volatile("" : "=f"(accP[i]), "=f"(accQ[i]));
        u_lda(A1, a0 + 16, a1 + 16);
#pragma unroll
        for (int i = 0; i < 4; i++) asm volatile("" : "=f"(S[i]));
#pragma unroll
        for (int k = 0; k < 8; k++) Aq[k] = hmul2_bf16(A0[k], ap[k]);
        wgmma_fence();
        u_mma(accP, A0, dsc(0, 0));
        wgmma_commit();
        u_mma(accQ, Aq, dsc(0, 1));
        wgmma_commit();
        if (wgc == 0) TS(62);
        auto pack8 = [&](uint32_t (&d)[8], const float (&a)[16]) {
#pragma unroll
            for (int k = 0; k < 8; k++) asm volatile("cvt.rn.bf16x2.f32 %0, %1, %2;" : "=r"(d[k]) : "f"(a[2 * k + 1]), "f"(a[2 * k]));
        };
        uint32_t da, db, tt;
        static_for<0, 8>([&](auto PC) {
            constexpr int p = decltype(PC)::value, e = 2 * p;
            if (p == 7) send_addr(sb, rank * 3 + 1 + wgc, w4, da, db, tt);
            auto mw = [&](int s, int k) { return k < 6 ? M[p][2 * k + s] : TL[(e + s) & 3][k - 6]; };
            uint32_t tp[8], tq[8];
            wgmma_wait<1>();
            pack8(tp, accP);
            wgmma_fence();
            u_mma(accP, A1, dsc(e + 1, 0));
            if (p) {
                wgmma_m64n8k16_rs(S, w, dq, p > 1);
                wgmma_m64n8k16_rs(S, w + 4, dq, 1);
            }
            wgmma_commit();
            if (p < 7) u_lda(A0, a0 + 16 * e + 32, a1 + 16 * e + 32);
            wgmma_wait<1>();
            pack8(tq, accQ);
#pragma unroll
            for (int k = 0; k < 8; k++) Aq[k] = hmul2_bf16(A1[k], ap[k]);
            wgmma_fence();
            u_mma(accQ, Aq, dsc(e + 1, 1));
            wgmma_commit();
#pragma unroll
            for (int k = 0; k < 8; k++) tq[k] = hfma2_bf16(tq[k], ap[k], tp[k]);
            if (p == 0 || p == 2 || p == 5) mbar_wait(BAR(B_CFULL + 1 + p / 2), 0);
            wgmma_wait<1>();
            pack8(tp, accP);
            if (p < 7) {
                wgmma_fence();
                u_mma(accP, A0, dsc(e + 2, 0));
                wgmma_commit();
                u_lda(A1, a0 + 16 * e + 48, a1 + 16 * e + 48);
            }
#pragma unroll
            for (int k = 0; k < 8; k++) w[k] = hmul2_bf16(tq[k], mw(0, k));
            wgmma_wait<(p < 7)>();
            if (p == 0 && elect_one()) mbar_arrive(BAR(B_CDONE));
            pack8(tq, accQ);
            if (p < 7) {
#pragma unroll
                for (int k = 0; k < 8; k++) Aq[k] = hmul2_bf16(A0[k], ap[k]);
                wgmma_fence();
                u_mma(accQ, Aq, dsc(e + 2, 1));
                wgmma_commit();
            }
#pragma unroll
            for (int k = 0; k < 8; k++) w[k] = hfma2_bf16(hfma2_bf16(tq[k], ap[k], tp[k]), mw(1, k), w[k]);
        });
        wgmma_fence();
        wgmma_m64n8k16_rs(S, w, dq, 1);
        wgmma_m64n8k16_rs(S, w + 4, dq, 1);
        wgmma_commit();
        wgmma_wait<0>();
        send_partial(da, db, tt, S[0], S[2]);
        if (wgc == 0) TS(14);
    }
#undef BAR
}

typedef CUresult (*PFN_encodeTiled)(CUtensorMap*, CUtensorMapDataType, cuuint32_t, void*, const cuuint64_t*, const cuuint64_t*,
                                    const cuuint32_t*, const cuuint32_t*, CUtensorMapInterleave, CUtensorMapSwizzle,
                                    CUtensorMapL2promotion, CUtensorMapFloatOOBfill);

}

extern "C" void kernel_launch(void* const* d_in, const int* in_sizes, int n_in, void* d_out, int out_size) {
    const int* idx = (const int*)d_in[0];
    const __nv_bfloat16* table = (const __nv_bfloat16*)d_in[1];
    const __nv_bfloat16* se_w1 = (const __nv_bfloat16*)d_in[2];
    const __nv_bfloat16* se_w2 = (const __nv_bfloat16*)d_in[3];
    const __nv_bfloat16* w_bi = (const __nv_bfloat16*)d_in[4];
    const __nv_bfloat16* w_cross = (const __nv_bfloat16*)d_in[5];
    const __nv_bfloat16* w_deep1 = (const __nv_bfloat16*)d_in[6];
    const __nv_bfloat16* w_deep2 = (const __nv_bfloat16*)d_in[7];
    __nv_bfloat16* out = (__nv_bfloat16*)d_out;

    static PFN_encodeTiled enc = nullptr;
    if (!enc) {
        void* fn = nullptr;
        cudaDriverEntryPointQueryResult qres;
        cudaGetDriverEntryPoint("cuTensorMapEncodeTiled", &fn, cudaEnableDefault, &qres);
        enc = (PFN_encodeTiled)fn;
        cudaFuncSetAttribute(fused_kernel, cudaFuncAttributeMaxDynamicSharedMemorySize, SMEM);
    }
    CUtensorMap tm;
    {
        cuuint64_t gdim[3] = {64, (cuuint64_t)(NF * ND), 4};
        cuuint64_t gstr[2] = {(cuuint64_t)NH * 2, 128};
        cuuint32_t box[3] = {64, 64, 1};
        cuuint32_t estr[3] = {1, 1, 1};
        enc(&tm, CU_TENSOR_MAP_DATA_TYPE_BFLOAT16, 3, (void*)w_deep1, gdim, gstr, box, estr, CU_TENSOR_MAP_INTERLEAVE_NONE,
            CU_TENSOR_MAP_SWIZZLE_128B, CU_TENSOR_MAP_L2_PROMOTION_L2_256B, CU_TENSOR_MAP_FLOAT_OOB_FILL_NONE);
    }
    fused_kernel<<<128, 512, SMEM>>>(idx, table, w_deep1, w_bi, w_deep2, w_cross, se_w1, se_w2, out, tm);
}
```

```cpp
#include <cuda_runtime.h>
#include <cuda_bf16.h>
#include <cuda.h>
#include <stdint.h>
#include <type_traits>
#include <utility>

#define R_DEEP 216
#define R_CR1 136
#define R_CR2 208
#define R_DEEP2 72
#define R_PROD 24

namespace {

constexpr int NF = 26, ND = 64, NH = 256, NFR = 13;

#define TS(slot)
#define TSL(slot)

__device__ __forceinline__ uint32_t smem_u32(const void* p) { return (uint32_t)__cvta_generic_to_shared(p); }
__device__ __forceinline__ void mbar_init(uint32_t bar, uint32_t cnt) {
    asm volatile("mbarrier.init.shared::cta.b64 [%0], %1;" ::"r"(bar), "r"(cnt));
}
__device__ __forceinline__ void mbar_expect_tx(uint32_t bar, uint32_t bytes) {
    asm volatile("mbarrier.arrive.expect_tx.shared::cta.b64 _, [%0], %1;" ::"r"(bar), "r"(bytes) : "memory");
}
__device__ __forceinline__ void mbar_arrive(uint32_t bar) {
    asm volatile("mbarrier.arrive.shared::cta.b64 _, [%0];" ::"r"(bar) : "memory");
}
__device__ __forceinline__ void mbar_wait(uint32_t bar, uint32_t parity) {
    asm volatile(
        "{\n"
        ".reg .pred p;\n"
        "WAIT_%=:\n"
        "mbarrier.try_wait.parity.shared::cta.b64 p, [%0], %1;\n"
        "@p bra.uni DONE_%=;\nbra.uni WAIT_%=;\nDONE_%=:\n"
        "}\n" ::"r"(bar),
        "r"(parity)
        : "memory");
}
__device__ __forceinline__ uint32_t opq(uint32_t x) { return __shfl_xor_sync(0xffffffffu, x, 0); }
__device__ __forceinline__ uint64_t uni64(uint64_t x) {
    uint32_t lo = (uint32_t)x, hi = (uint32_t)(x >> 32);
    asm volatile("shfl.sync.idx.b32 %0, %0, 0, 31, -1;\nshfl.sync.idx.b32 %1, %1, 0, 31, -1;" : "+r"(lo), "+r"(hi));
    return ((uint64_t)hi << 32) | lo;
}
__device__ __forceinline__ bool elect_one() {
    uint32_t r;
    asm volatile("{\n.reg .pred p;\nelect.sync _|p, 0xffffffff;\nselp.u32 %0, 1, 0, p;\n}\n" : "=r"(r));
    return r;
}
__device__ __forceinline__ const void* row_ptr(const void* base, uint32_t i) {
    const void* r;
    asm("mad.wide.u32 %0, %1, 128, %2;" : "=l"(r) : "r"(i), "l"(base));
    return r;
}
__device__ __forceinline__ void mbar_wait_bounded(uint32_t bar, uint32_t parity) {
    asm volatile(
        "{\n"
        ".reg .pred p;\n"
        ".reg .u32 c;\n"
        "mov.u32 c, 0;\n"
        "WAIT_%=:\n"
        "mbarrier.try_wait.parity.shared::cta.b64 p, [%0], %1;\n"
        "@p bra.uni DONE_%=;\n"
        "add.u32 c, c, 1;\n"
        "setp.lt.u32 p, c, 0x400000;\n"
        "@p bra.uni WAIT_%=;\n"
        "trap;\n"
        "DONE_%=:\n"
        "}\n" ::"r"(bar),
        "r"(parity)
        : "memory");
}
__device__ __forceinline__ void cp_async16(uint32_t dst, const void* src) {
    asm volatile("cp.async.cg.shared.global [%0], [%1], 16;" ::"r"(dst), "l"(src) : "memory");
}
__device__ __forceinline__ void cp_async_mbar_arrive_noinc(uint32_t bar) {
    asm volatile("cp.async.mbarrier.arrive.noinc.shared::cta.b64 [%0];" ::"r"(bar) : "memory");
}
__device__ __forceinline__ void tma_load_3d(uint32_t dst, const void* tmap, int c0, int c1, int c2, uint32_t bar) {
    asm volatile(
        "cp.async.bulk.tensor.3d.shared::cluster.global.mbarrier::complete_tx::bytes [%0], [%1, {%3, %4, %5}], [%2];" ::"r"(dst),
        "l"(tmap), "r"(bar), "r"(c0), "r"(c1), "r"(c2)
        : "memory");
}
__device__ __forceinline__ void bulk_load(uint32_t dst, const void* src, uint32_t bytes, uint32_t bar) {
    asm volatile("cp.async.bulk.shared::cluster.global.mbarrier::complete_tx::bytes [%0], [%1], %2, [%3];" ::"r"(dst), "l"(src), "r"(bytes),
                 "r"(bar)
                 : "memory");
}
__device__ __forceinline__ void fence_proxy_async() { asm volatile("fence.proxy.async.shared::cta;" ::: "memory"); }
__device__ __forceinline__ void wgmma_fence() { asm volatile("wgmma.fence.sync.aligned;" ::: "memory"); }
__device__ __forceinline__ void wgmma_commit() { asm volatile("wgmma.commit_group.sync.aligned;" ::: "memory"); }
template <int N> __device__ __forceinline__ void wgmma_wait() { asm volatile("wgmma.wait_group.sync.aligned %0;" ::"n"(N) : "memory"); }

__device__ __forceinline__ void ldsm_x4_t(uint32_t addr, uint32_t& r0, uint32_t& r1, uint32_t& r2, uint32_t& r3) {
    asm volatile("ldmatrix.sync.aligned.m8n8.x4.trans.shared.b16 {%0,%1,%2,%3}, [%4];" : "=r"(r0), "=r"(r1), "=r"(r2), "=r"(r3) : "r"(addr));
}
__device__ __forceinline__ void stsm_x4_t(uint32_t addr, uint32_t r0, uint32_t r1, uint32_t r2, uint32_t r3) {
    asm volatile("stmatrix.sync.aligned.m8n8.x4.trans.shared.b16 [%0], {%1,%2,%3,%4};" ::"r"(addr), "r"(r0), "r"(r1), "r"(r2), "r"(r3) : "memory");
}
__device__ __forceinline__ uint4 lds128(uint32_t addr) {
    uint4 v;
    asm volatile("ld.shared.v4.u32 {%0,%1,%2,%3}, [%4];" : "=r"(v.x), "=r"(v.y), "=r"(v.z), "=r"(v.w) : "r"(addr));
    return v;
}
__device__ __forceinline__ uint32_t lds32(uint32_t addr) {
    uint32_t v;
    asm volatile("ld.shared.u32 %0, [%1];" : "=r"(v) : "r"(addr));
    return v;
}
__device__ __forceinline__ void sts128(uint32_t addr, uint32_t a, uint32_t b, uint32_t c, uint32_t d) {
    asm volatile("st.shared.v4.u32 [%0], {%1,%2,%3,%4};" ::"r"(addr), "r"(a), "r"(b), "r"(c), "r"(d) : "memory");
}
__device__ __forceinline__ uint32_t pack_bf16(float lo, float hi) {
    uint32_t r;
    asm("cvt.rn.bf16x2.f32 %0, %1, %2;" : "=r"(r) : "f"(hi), "f"(lo));
    return r;
}
__device__ __forceinline__ uint32_t hmul2_bf16(uint32_t a, uint32_t b) {
    uint32_t r;
    asm("mul.rn.bf16x2 %0, %1, %2;" : "=r"(r) : "r"(a), "r"(b));
    return r;
}
__device__ __forceinline__ float tanh_fast(float x) {
    float r;
    asm("tanh.approx.f32 %0, %1;" : "=f"(r) : "f"(x));
    return r;
}
#define WG_ACC8(c, b) c(acc[b]), c(acc[b + 1]), c(acc[b + 2]), c(acc[b + 3]), c(acc[b + 4]), c(acc[b + 5]), c(acc[b + 6]), c(acc[b + 7])
__device__ __forceinline__ void wgmma_n168(float (&acc)[84], uint64_t da, uint64_t db, int sc) {
    asm volatile("{\n.reg .pred p;\nsetp.ne.b32 p, %86, 0;\nwgmma.mma_async.sync.aligned.m64n168k16.f32.bf16.bf16 {%0,%1,%2,%3,%4,%5,%6,%7,%8,%9,%10,%11,%12,%13,%14,%15,%16,%17,%18,%19,%20,%21,%22,%23,%24,%25,%26,%27,%28,%29,%30,%31,%32,%33,%34,%35,%36,%37,%38,%39,%40,%41,%42,%43,%44,%45,%46,%47,%48,%49,%50,%51,%52,%53,%54,%55,%56,%57,%58,%59,%60,%61,%62,%63,%64,%65,%66,%67,%68,%69,%70,%71,%72,%73,%74,%75,%76,%77,%78,%79,%80,%81,%82,%83}, %84, %85, p, 1, 1, 0, 1;\n}\n"
                 : "+f"(acc[0]), "+f"(acc[1]), "+f"(acc[2]), "+f"(acc[3]), "+f"(acc[4]), "+f"(acc[5]), "+f"(acc[6]), "+f"(acc[7]), "+f"(acc[8]), "+f"(acc[9]), "+f"(acc[10]), "+f"(acc[11]), "+f"(acc[12]), "+f"(acc[13]), "+f"(acc[14]), "+f"(acc[15]), "+f"(acc[16]), "+f"(acc[17]), "+f"(acc[18]), "+f"(acc[19]), "+f"(acc[20]), "+f"(acc[21]), "+f"(acc[22]), "+f"(acc[23]), "+f"(acc[24]), "+f"(acc[25]), "+f"(acc[26]), "+f"(acc[27]), "+f"(acc[28]), "+f"(acc[29]), "+f"(acc[30]), "+f"(acc[31]), "+f"(acc[32]), "+f"(acc[33]), "+f"(acc[34]), "+f"(acc[35]), "+f"(acc[36]), "+f"(acc[37]), "+f"(acc[38]), "+f"(acc[39]), "+f"(acc[40]), "+f"(acc[41]), "+f"(acc[42]), "+f"(acc[43]), "+f"(acc[44]), "+f"(acc[45]), "+f"(acc[46]), "+f"(acc[47]), "+f"(acc[48]), "+f"(acc[49]), "+f"(acc[50]), "+f"(acc[51]), "+f"(acc[52]), "+f"(acc[53]), "+f"(acc[54]), "+f"(acc[55]), "+f"(acc[56]), "+f"(acc[57]), "+f"(acc[58]), "+f"(acc[59]), "+f"(acc[60]), "+f"(acc[61]), "+f"(acc[62]), "+f"(acc[63]), "+f"(acc[64]), "+f"(acc[65]), "+f"(acc[66]), "+f"(acc[67]), "+f"(acc[68]), "+f"(acc[69]), "+f"(acc[70]), "+f"(acc[71]), "+f"(acc[72]), "+f"(acc[73]), "+f"(acc[74]), "+f"(acc[75]), "+f"(acc[76]), "+f"(acc[77]), "+f"(acc[78]), "+f"(acc[79]), "+f"(acc[80]), "+f"(acc[81]), "+f"(acc[82]), "+f"(acc[83])
                 : "l"(da), "l"(db), "r"(sc));
}
__device__ __forceinline__ void wgmma_n128(float (&acc)[64], uint64_t da, uint64_t db, int sc) {
    asm volatile("{\n.reg .pred p;\nsetp.ne.b32 p, %66, 0;\nwgmma.mma_async.sync.aligned.m64n128k16.f32.bf16.bf16 {%0,%1,%2,%3,%4,%5,%6,%7,%8,%9,%10,%11,%12,%13,%14,%15,%16,%17,%18,%19,%20,%21,%22,%23,%24,%25,%26,%27,%28,%29,%30,%31,%32,%33,%34,%35,%36,%37,%38,%39,%40,%41,%42,%43,%44,%45,%46,%47,%48,%49,%50,%51,%52,%53,%54,%55,%56,%57,%58,%59,%60,%61,%62,%63}, %64, %65, p, 1, 1, 0, 1;\n}\n"
                 : "+f"(acc[0]), "+f"(acc[1]), "+f"(acc[2]), "+f"(acc[3]), "+f"(acc[4]), "+f"(acc[5]), "+f"(acc[6]), "+f"(acc[7]), "+f"(acc[8]), "+f"(acc[9]), "+f"(acc[10]), "+f"(acc[11]), "+f"(acc[12]), "+f"(acc[13]), "+f"(acc[14]), "+f"(acc[15]), "+f"(acc[16]), "+f"(acc[17]), "+f"(acc[18]), "+f"(acc[19]), "+f"(acc[20]), "+f"(acc[21]), "+f"(acc[22]), "+f"(acc[23]), "+f"(acc[24]), "+f"(acc[25]), "+f"(acc[26]), "+f"(acc[27]), "+f"(acc[28]), "+f"(acc[29]), "+f"(acc[30]), "+f"(acc[31]), "+f"(acc[32]), "+f"(acc[33]), "+f"(acc[34]), "+f"(acc[35]), "+f"(acc[36]), "+f"(acc[37]), "+f"(acc[38]), "+f"(acc[39]), "+f"(acc[40]), "+f"(acc[41]), "+f"(acc[42]), "+f"(acc[43]), "+f"(acc[44]), "+f"(acc[45]), "+f"(acc[46]), "+f"(acc[47]), "+f"(acc[48]), "+f"(acc[49]), "+f"(acc[50]), "+f"(acc[51]), "+f"(acc[52]), "+f"(acc[53]), "+f"(acc[54]), "+f"(acc[55]), "+f"(acc[56]), "+f"(acc[57]), "+f"(acc[58]), "+f"(acc[59]), "+f"(acc[60]), "+f"(acc[61]), "+f"(acc[62]), "+f"(acc[63])
                 : "l"(da), "l"(db), "r"(sc));
}
__device__ __forceinline__ void wgmma_n40(float (&acc)[20], uint64_t da, uint64_t db, int sc) {
    asm volatile("{\n.reg .pred p;\nsetp.ne.b32 p, %22, 0;\nwgmma.mma_async.sync.aligned.m64n40k16.f32.bf16.bf16 {%0,%1,%2,%3,%4,%5,%6,%7,%8,%9,%10,%11,%12,%13,%14,%15,%16,%17,%18,%19}, %20, %21, p, 1, 1, 0, 1;\n}\n"
                 : "+f"(acc[0]), "+f"(acc[1]), "+f"(acc[2]), "+f"(acc[3]), "+f"(acc[4]), "+f"(acc[5]), "+f"(acc[6]), "+f"(acc[7]), "+f"(acc[8]), "+f"(acc[9]), "+f"(acc[10]), "+f"(acc[11]), "+f"(acc[12]), "+f"(acc[13]), "+f"(acc[14]), "+f"(acc[15]), "+f"(acc[16]), "+f"(acc[17]), "+f"(acc[18]), "+f"(acc[19])
                 : "l"(da), "l"(db), "r"(sc));
}
__device__ __forceinline__ void wgmma_n40_0(float (&acc)[20], uint64_t da, uint64_t db) {
    asm volatile("{\n.reg .pred p;\nsetp.ne.b32 p, 0, 0;\nwgmma.mma_async.sync.aligned.m64n40k16.f32.bf16.bf16 {%0,%1,%2,%3,%4,%5,%6,%7,%8,%9,%10,%11,%12,%13,%14,%15,%16,%17,%18,%19}, %20, %21, p, 1, 1, 0, 1;\n}\n"
                 : "=f"(acc[0]), "=f"(acc[1]), "=f"(acc[2]), "=f"(acc[3]), "=f"(acc[4]), "=f"(acc[5]), "=f"(acc[6]), "=f"(acc[7]), "=f"(acc[8]), "=f"(acc[9]), "=f"(acc[10]), "=f"(acc[11]), "=f"(acc[12]), "=f"(acc[13]), "=f"(acc[14]), "=f"(acc[15]), "=f"(acc[16]), "=f"(acc[17]), "=f"(acc[18]), "=f"(acc[19])
                 : "l"(da), "l"(db));
}
#define WG_N32(c, sc)                                                   \
    asm volatile(                                                       \
        "{\n"                                                           \
        ".reg .pred p;\n"           \
        "setp.ne.b32 p, " sc ", 0;\n"                                   \
        "wgmma.mma_async.sync.aligned.m64n32k16.f32.bf16.bf16 "         \
        "{%0,%1,%2,%3,%4,%5,%6,%7,%8,%9,%10,%11,%12,%13,%14,%15},"      \
        " {%16,%17,%18,%19}, %20, p, 1, 1, 0;\n"                        \
        "}\n"                                                           \
        : WG_ACC8(c, 0), WG_ACC8(c, 8)                                  \
        : "r"(a0), "r"(a1), "r"(a2), "r"(a3), "l"(db))
template <int SC>
__device__ __forceinline__ void wgmma_m64n32k16_rs(float (&acc)[16], uint32_t a0, uint32_t a1, uint32_t a2, uint32_t a3, uint64_t db) {
    if constexpr (SC == 1) WG_N32("+f", "1");
    else if constexpr (SC == 2) WG_N32("+f", "0");
    else WG_N32("=f", "0");
}

__host__ __device__ constexpr uint64_t make_desc(uint32_t addr, uint32_t lbo_bytes, uint32_t sbo_bytes, uint32_t swz) {
    uint64_t d = 0;
    d |= (uint64_t)((addr & 0x3FFFF) >> 4);
    d |= (uint64_t)((lbo_bytes >> 4) & 0x3FFF) << 16;
    d |= (uint64_t)((sbo_bytes >> 4) & 0x3FFF) << 32;
    d |= (uint64_t)swz << 62;
    return d;
}
__device__ __forceinline__ uint32_t ldg_u16(const __nv_bfloat16* p) { return (uint32_t)__ldg(reinterpret_cast<const unsigned short*>(p)); }
template <int N, class F, int... I>
__device__ __forceinline__ void static_for_impl(F&& f, std::integer_sequence<int, I...>) {
    (f(std::integral_constant<int, N + I>{}), ...);
}
template <int B, int E, class F>
__device__ __forceinline__ void static_for(F&& f) {
    static_for_impl<B>(f, std::make_integer_sequence<int, E - B>{});
}

__device__ __forceinline__ uint32_t hfma2_bf16(uint32_t a, uint32_t b, uint32_t c) {
    uint32_t r;
    asm("fma.rn.bf16x2 %0, %1, %2, %3;" : "=r"(r) : "r"(a), "r"(b), "r"(c));
    return r;
}
__device__ __forceinline__ float gelu2(float x) {
    const float k0 = 0.7978845608028654f, k01 = 0.7978845608028654f * 0.044715f;
    return fmaf(x, tanh_fast(x * fmaf(x * x, k01, k0)), x);
}
__device__ __forceinline__ uint32_t gelu2p(uint32_t x) {
    uint32_t t;
    const uint32_t u = hmul2_bf16(x, hfma2_bf16(hmul2_bf16(x, x), 0x3D123D12u, 0x3F4C3F4Cu));
    asm("tanh.approx.bf16x2 %0, %1;" : "=r"(t) : "r"(u));
    return hfma2_bf16(x, t, x);
}
__device__ __forceinline__ void wgmma_m64n8k16_rs(float (&acc)[4], const uint32_t* a, uint64_t db, int sc) {
    asm volatile("{\n.reg .pred p;\nsetp.ne.b32 p, %9, 0;\nwgmma.mma_async.sync.aligned.m64n8k16.f32.bf16.bf16 {%0,%1,%2,%3}, {%4,%5,%6,%7}, %8, p, 1, 1, 0;\n}\n"
                 : "+f"(acc[0]), "+f"(acc[1]), "+f"(acc[2]), "+f"(acc[3])
                 : "r"(a[0]), "r"(a[1]), "r"(a[2]), "r"(a[3]), "l"(db), "r"(sc));
}

template <int SC>
__device__ __forceinline__ void wgmma_m64n16k16_rs(float (&acc)[8], const uint32_t* a, uint64_t db) {
    asm volatile("{\n.reg .pred p;\nsetp.ne.b32 p, %13, 0;\nwgmma.mma_async.sync.aligned.m64n16k16.f32.bf16.bf16 {%0,%1,%2,%3,%4,%5,%6,%7}, {%8,%9,%10,%11}, %12, p, 1, 1, 0;\n}\n"
                 : WG_ACC8("+f", 0)
                 : "r"(a[0]), "r"(a[1]), "r"(a[2]), "r"(a[3]), "l"(db), "n"(SC));
}

constexpr int SB0 = 1024;
constexpr int SLOT = 4096;
constexpr int EWP = SLOT + 16;
constexpr int OFF_EW = 608;
constexpr int OFF_RT = 1024;
constexpr int RT = 8192;
__host__ __device__ constexpr int tile(int f) { return f == 13 ? 17 : f < 21 ? (f + 11 * (f & 1)) / 2 : (f & 1) ? (f + 1) / 2 : f - 5; }
__host__ __device__ constexpr int w1_dist(int f) { return f < 16 ? (int)(0x5713457134571345ull >> (4 * f)) & 7 : (0x5134 >> (4 * (f & 3))) & 7; }
constexpr int HS_BYTES = 16384;
constexpr int OFF_WBI = OFF_RT + 26 * RT;
constexpr int OFF_IDX = OFF_RT + 15 * RT;
constexpr int OFF_SEF = OFF_WBI + RT;
constexpr int OFF_AP = OFF_SEF + 2048;
constexpr int OFF_W2 = 0;
constexpr int OFF_DP = OFF_AP + 4096;
constexpr int OFF_ID = OFF_DP + 6 * 32 * 4;
constexpr int OFF_BAR = OFF_ID + 256;
constexpr int TILE = 2048;
constexpr int CHUNK = 4 * TILE;
constexpr int NCHUNK = 16;
constexpr uint64_t CPOS = 0x21A70D986543CB21ull;
static_assert(OFF_EW + 25 * EWP + SLOT <= OFF_RT + 13 * RT && CHUNK == RT, "layout");
static_assert(OFF_ID % 128 == 0, "align");
constexpr int B_CFULL = 0,
              B_F = 4,
              B_W = 16,
              B_EMPTY = 48, B_ZRDY = B_EMPTY + NF, B_CDONE = B_ZRDY + 1,
              B_EWRDY = B_CDONE + 2, B_PAIR = 80,
              B_IDX = B_PAIR + 13, B_FIN = B_PAIR + 14;
constexpr int OFF_TS = OFF_BAR + 768;
constexpr int SMEM = OFF_TS + 512;
static_assert(SMEM <= 232448, "smem");
constexpr int NFIRST = 4;
constexpr int NP = 2;
constexpr int NUNIT = 128;

__device__ __align__(1024) uint8_t g_wt[2 * NCHUNK * CHUNK];
__device__ unsigned int g_cnt;

__device__ __forceinline__ void u_lda(uint32_t (&A)[8], uint32_t a0, uint32_t a1) {
    ldsm_x4_t(a0, A[0], A[1], A[2], A[3]);
    ldsm_x4_t(a1, A[4], A[5], A[6], A[7]);
}
__device__ __forceinline__ void u_mma(float (&acc)[16], const uint32_t (&A)[8], uint64_t desc) {
    wgmma_m64n32k16_rs<2>(acc, A[0], A[1], A[2], A[3], desc);
    wgmma_m64n32k16_rs<1>(acc, A[4], A[5], A[6], A[7], desc + 64);
}
__device__ __forceinline__ void send_addr(uint32_t sb, int src, int w4, uint32_t& da, uint32_t& db, uint32_t& t) {
    uint32_t rb, l;
    asm volatile("mov.u32 %0, %%laneid;" : "=r"(l));
    asm volatile("mapa.shared::cluster.u32 %0, %1, %2;" : "=r"(rb) : "r"(sb), "r"(w4 >> 1));
    da = opq(rb + OFF_DP + (src * 32 + (w4 & 1) * 16 + 8 * (l & 1) + (l >> 2)) * 4);
    db = opq(rb + OFF_BAR + B_FIN * 8 + (l >> 5));
    t = l & 3;
}
__device__ __forceinline__ void send_partial(uint32_t da, uint32_t db, uint32_t t, float v0, float v1) {
    asm volatile("{\n.reg .pred p;\nsetp.lt.u32 p, %3, 2;\n@p st.async.weak.shared::cluster.mbarrier::complete_tx::bytes.f32 [%0], %1, [%2];\n}\n" ::"r"(da), "f"(t ? v1 : v0),
                 "r"(db), "r"(t)
                 : "memory");
}

__global__ void __cluster_dims__(2, 1, 1) __launch_bounds__(512, 1)
fused_kernel(const int* __restrict__ idx, const __nv_bfloat16* __restrict__ table, const __nv_bfloat16* __restrict__ w1, const __nv_bfloat16* __restrict__ w_bi,
             const __nv_bfloat16* __restrict__ w2, const __nv_bfloat16* __restrict__ w_cross, const __nv_bfloat16* __restrict__ se_w1,
             const __nv_bfloat16* __restrict__ se_w2, __nv_bfloat16* __restrict__ out, const __grid_constant__ CUtensorMap tmW1) {
    extern __shared__ __align__(1024) uint8_t smem_raw[];
    const int tid = threadIdx.x, b = (tid >> 3) & 31;
    const int pb0 = (blockIdx.x >> 1) * 64;
    int2 i0a, i0b, i1a, i1b;
    asm volatile("ld.global.nc.v2.u32 {%0,%1}, [%8];\nld.global.nc.v2.u32 {%2,%3}, [%8 + 3328];\nld.global.nc.v2.u32 {%4,%5}, [%8 + 8];\nld.global.nc.v2.u32 {%6,%7}, [%8 + 3336];"
                 : "=r"(i0a.x), "=r"(i0a.y), "=r"(i0b.x), "=r"(i0b.y), "=r"(i1a.x), "=r"(i1a.y), "=r"(i1b.x), "=r"(i1b.y)
                 : "l"(idx + (pb0 + b) * NF));
    const uint32_t sb = __shfl_sync(0xffffffffu, smem_u32(smem_raw), 0);
    const uint32_t bars = sb + OFF_BAR;
#define BAR(i) (bars + (i) * 8)
    const int warp = __shfl_sync(0xffffffffu, tid >> 5, 0), lane = tid & 31, g = lane >> 2, t = lane & 3;
    const int rank = blockIdx.x & 1;
    if (tid == 0) TS(0);
    if (elect_one()) {
        mbar_init(BAR(B_PAIR + warp), warp < 13 ? 256 + (warp == 10) : 1);
        if (warp >= 13) {
            asm volatile("fence.mbarrier_init.release.cluster;" ::: "memory");
            mbar_expect_tx(BAR(B_PAIR + warp), warp == 13 ? 64 * NF * 4 : 6 * 32 * 4);
            if (warp == 13) bulk_load(sb + OFF_IDX, idx + pb0 * NF, 64 * NF * 4, BAR(B_IDX));
        }
        if (warp == 6) asm volatile("cp.async.bulk.prefetch.L2.global [%0], %1;" ::"l"((const char*)w1 + 19 * 32768 + blockIdx.x * 1792), "n"(1792) : "memory");
        mbar_init(BAR(16 + warp), (warp & 1) || !warp ? 1 : 9);
        mbar_init(BAR(32 + warp), (warp & 1) && warp != 9 ? 1 : 9);
        mbar_init(BAR(48 + warp), 4);
        mbar_init(BAR(64 + warp), warp == B_CDONE - 64 ? 8 : 4);
        if (warp < 4 + NP) mbar_init(BAR(warp), warp < 4 ? (0x3421 >> (4 * warp)) & 7 : 256);
        asm volatile("fence.mbarrier_init.release.cluster;" ::: "memory");
    }
    __syncthreads();
    asm volatile("barrier.cluster.arrive.relaxed.aligned;" ::: "memory");
    if (tid == 0) TS(1);

    if (warp >= 12) {
        asm volatile("setmaxnreg.dec.sync.aligned.u32 %0;" ::"n"(R_PROD));
        if ((sb & 0xFFFFFFu) != SB0) __trap();
        if (warp == 12) {
            const uint32_t c0 = clock();
#pragma unroll 1
            for (int f = 0; f < NF; f++) {
                const uint32_t dist = w1_dist(f) * RT;
                if (f >= 5) mbar_wait_bounded(BAR(B_EMPTY + f - (f < 19 ? 5 : 4)), 0);
                while (f < 5 && (uint32_t)clock() - c0 < f * 450) __nanosleep(32);
                TSL(80 + f);
                if (elect_one()) {
                    mbar_expect_tx(BAR(B_W + f), HS_BYTES);
                    tma_load_3d(sb + OFF_WBI - 2 * dist, &tmW1, 0, f * 64, rank * 2, BAR(B_W + f));
                    tma_load_3d(sb + OFF_WBI - dist, &tmW1, 0, f * 64, rank * 2 + 1, BAR(B_W + f));
                }
            }
            asm volatile("barrier.cluster.wait.acquire.aligned;" ::: "memory");
            const uint64_t po = (uint64_t)(out + pb0 + 32 * rank + lane);
            const uint32_t plo = opq((uint32_t)po), phi = opq((uint32_t)(po >> 32) + (lane >> 5)), dp = opq(sb + OFF_DP + lane * 4);
            mbar_wait_bounded(BAR(B_FIN), 0);
            const uint4 u = make_uint4(lds32(dp), lds32(dp + 128), lds32(dp + 256), lds32(dp + 384));
            const uint2 v = make_uint2(lds32(dp + 512), lds32(dp + 640));
            asm volatile("st.global.u16 [%0], %1;" ::"l"(((uint64_t)phi << 32) | plo),
                         "h"(__bfloat16_as_ushort(__float2bfloat16_rn((__uint_as_float(u.x) + __uint_as_float(u.y)) + (__uint_as_float(u.z) + __uint_as_float(u.w)) +
                                                                      (__uint_as_float(v.x) + __uint_as_float(v.y)))))
                         : "memory");
            TSL(15);
        } else {
            if (warp == 13) {
                const uint32_t sr = sb + OFF_AP;
                {
                    uint32_t v[12];
#pragma unroll
                    for (int i = 0; i < 12; i++) v[i] = lane + 32 * (i >> 1) < NF * NFR / 2 ? __ldg(reinterpret_cast<const uint32_t*>((i & 1) ? se_w2 : se_w1) + lane + 32 * (i >> 1)) : 0u;
#pragma unroll
                    for (int i = 0; i < 12; i++) asm volatile("st.shared.u32 [%0], %1;" ::"r"(sr + lane * 4 + (i >> 1) * 128 + (i & 1) * 1024), "r"(v[i]) : "memory");
                    __syncwarp();
                }
#pragma unroll 1
                for (int q = 0; q < 8; q++) {
                    const int c1 = 8 * (q & 1) + g, o1 = c1 < NFR ? min((8 * (q >> 1) + 2 * t) * NFR + c1, NF * NFR) : NF * NFR;
                    const int c2 = 8 * (q & 3) + ((q & 3) < 3 ? 4 * (g & 1) + (g >> 1) : (g & 1)), o2 = min((8 * (q >> 2) + 2 * t) * NF + c2, NF * NFR);
                    uint32_t y1, y2;
                    asm volatile("{\n.reg .b16 a, b, c, d;\nld.shared.b16 a, [%2];\nld.shared.b16 b, [%2 + 26];\nld.shared.b16 c, [%3 + 1024];\nld.shared.b16 d, [%3 + 1076];\n"
                                 "mov.b32 %0, {a, b};\nmov.b32 %1, {c, d};\n}\n" : "=r"(y1), "=r"(y2) : "r"(sr + 2 * o1), "r"(sr + 2 * o2));
                    asm volatile("st.shared.u32 [%0], %1;\nst.shared.u32 [%0 + 1024], %2;" ::"r"(sb + OFF_SEF + q * 128 + lane * 4), "r"(y1),
                                 "r"(hmul2_bf16(y2, 0x3E803E80u))
                                 : "memory");
                }
                fence_proxy_async();
                __syncwarp();
                TSL(12);
                if (elect_one()) mbar_arrive(BAR(B_PAIR + 10));
            } else if (warp == 15) {
                {
                    const int pq = blockIdx.x >> 6, js = (blockIdx.x >> 1) & 31;
                    const int j = js < 24 ? (js & 24) + 4 * (js & 1) + ((js >> 1) & 3) : 24 + (js & 1);
                    const bool on = js < 24 || ((js >> 1) & 3) == ((lane >> 2) & 3);
                    const __nv_bfloat16* s = w_cross + ((size_t)(pq * NF) * NF + j) * ND + 32 * rank + lane;
                    uint8_t* d = g_wt + (size_t)rank * NCHUNK * CHUNK + (((lane & 15) >> 1) * 2 + (lane >> 4)) * CHUNK + ((lane & 1) * 2 + pq) * TILE + js * 16;
#pragma unroll 1
                    for (int kh = 0; kh < 2; kh++) {
                        uint32_t x[8];
#pragma unroll
                        for (int k = 0; k < 8; k++)
                            x[k] = (on && (kh == 0 || k < 5)) ? ldg_u16(s + (k + (k & 4)) * NF * ND) | (ldg_u16(s + (k == 4 && kh ? 9 : k + (k & 4) + 4) * NF * ND) << 16) : 0u;
                        *reinterpret_cast<uint4*>(d) = make_uint4(x[0], x[1], x[2], x[3]);
                        *reinterpret_cast<uint4*>(d + 512) = make_uint4(x[4], x[5], x[6], x[7]);
                        s += 16 * NF * ND;
                        d += 1024;
                    }
                    __syncwarp();
                }
                TSL(8);
                if (elect_one()) asm volatile("red.release.gpu.global.inc.u32 [%0], %1;" ::"l"(&g_cnt), "n"(NUNIT + 127) : "memory");
                TSL(9);
                mbar_wait(BAR(B_EMPTY + 6), 0);
                TSL(10);
                unsigned int v;
                do {
                    asm volatile("ld.acquire.gpu.global.u32 %0, [%1];" : "=r"(v) : "l"(&g_cnt) : "memory");
                } while (v < NUNIT);
                asm volatile("fence.proxy.async.global;" ::: "memory");
                __syncwarp();
                if (elect_one()) asm volatile("red.relaxed.gpu.global.inc.u32 [%0], %1;" ::"l"(&g_cnt), "n"(NUNIT + 127) : "memory");
                TSL(11);
                const uint8_t* wsrc = g_wt + (size_t)rank * NCHUNK * CHUNK;
                static_for<0, 10>([&](auto KC) {
                    constexpr int k = decltype(KC)::value, T[10][4] = {{0, 2, 5, 0}, {10, 1, 12, 2}, {2, 2, 8, 1}, {4, 2, 9, 1}, {6, 2, 10, 2}, {8, 2, 10, 2}, {11, 1, 11, 2}, {12, 1, 11, 3}, {13, 1, 11, 3}, {14, 2, 13, 3}};
                    if (k == 0 || T[k][2] != T[k ? k - 1 : 0][2]) mbar_wait(BAR(B_EMPTY + 14 + T[k][2]), 0);
                    TSL(30 + k);
                    if (elect_one()) {
                        mbar_expect_tx(BAR(B_CFULL + T[k][3]), T[k][1] * CHUNK);
                        bulk_load(sb + OFF_RT + (13 + ((int)(CPOS >> (4 * T[k][0])) & 15)) * RT, wsrc + T[k][0] * CHUNK, T[k][1] * CHUNK, BAR(B_CFULL + T[k][3]));
                    }
                });
            }
            __syncwarp();
            asm volatile("barrier.cluster.wait.acquire.aligned;" ::: "memory");
        }
    } else if (warp < 4) {
        {
            const uint4* wb = reinterpret_cast<const uint4*>(w_bi + (tid >> 2) * 64 + 32 * rank + 8 * t);
            const uint4 wb0 = __ldg(wb), wb1 = __ldg(wb + 256);
            const uint32_t w2v = __ldg(reinterpret_cast<const uint32_t*>(w2) + rank * 64 + (tid & 63));
            sts128(sb + OFF_WBI + (tid & 63) * 128 + ((4 ^ (tid & 7)) << 4), 0x3C803C80u, 0x3C803C80u, 0x3C803C80u, 0x3C803C80u);
            asm volatile("st.shared.u32 [%0], %1;" ::"r"(sb + OFF_ID + (tid & 63) * 4), "r"(0x3F803F80u) : "memory");
            asm volatile("st.shared.u32 [%0], %1;" ::"r"(sb + OFF_W2 + (tid & 63) * 4), "r"(w2v) : "memory");
            const uint32_t wd = sb + OFF_WBI + (tid >> 2) * 128 + ((t ^ (g & 7)) << 4);
            sts128(wd, wb0.x, wb0.y, wb0.z, wb0.w);
            sts128(wd + 4096, wb1.x, wb1.y, wb1.z, wb1.w);
            fence_proxy_async();
        }
        asm volatile("setmaxnreg.inc.sync.aligned.u32 %0;" ::"n"(R_DEEP));
        asm volatile("bar.sync 1, 128;" ::: "memory");
        asm volatile("barrier.cluster.wait.acquire.aligned;" ::: "memory");
        TS(7);
        float acc[2][84], e2[2][20], ad[64];
#pragma unroll
        for (int i = 0; i < 84; i++) asm volatile("" : "=f"(acc[0][i]), "=f"(acc[1][i]));
        const uint32_t sa = opq(sb + OFF_EW + (lane >> 4) * 128 + (2 * warp + ((lane >> 3) & 1)) * 512 + (lane & 7) * 16);
        const uint32_t ln = opq(lane);
        const bool l0 = ln == 0;
        uint32_t za[8];
#pragma unroll
        for (int i = 0; i < 6; i++) asm volatile("" : "=r"(za[i]));
        auto cvt = [&](uint32_t (&pk)[8], int f) {
            const float* e = f < 22 ? acc[f & 1] + 64 : e2[f & 1];
#pragma unroll
            for (int i = 0; i < 8; i++) asm volatile("cvt.rn.bf16x2.f32 %0, %1, %2;" : "=r"(pk[i]) : "f"(e[2 * i + 1]), "f"(e[2 * i]));
            uint32_t &z0 = za[2 * (f >> 3)], &z1 = za[2 * (f >> 3) + 1];
            asm volatile("{\n.reg .pred p;\nsetp.eq.u32 p, %6, %7;\n@p cvt.rn.bf16x2.f32 %0, %2, %4;\n@p cvt.rn.bf16x2.f32 %1, %3, %5;\n}\n"
                         : "+r"(z0), "+r"(z1)
                         : "f"(e[16]), "f"(e[18]), "f"((f & 1) ? __uint_as_float(z0) : 0.f), "f"((f & 1) ? __uint_as_float(z1) : 0.f), "r"(ln & 3), "r"((f >> 1) & 3));
        };
        auto store = [&](const uint32_t (&pk)[8], int f) {
            stsm_x4_t(sa + f * EWP, pk[0], pk[1], pk[2], pk[3]);
            stsm_x4_t(sa + f * EWP + 256, pk[4], pk[5], pk[6], pk[7]);
        };
        auto da = [](int f, int i) { return make_desc(SB0 + OFF_RT + tile(f) * RT, 16, 1024, 1) + 2 * (i ^ (2 * (f & 1))); };
        auto db = [](int f, int i) { return make_desc(SB0 + OFF_WBI - 2 * w1_dist(f) * RT, w1_dist(f) * RT, 1024, 1) + 128 * i; };
        auto mma_e = [&](int f) {
            wgmma_fence();
#pragma unroll
            for (int i = 0; i < 4; i++) {
                if (i) wgmma_n40(e2[f & 1], da(f, i), make_desc(SB0 + OFF_WBI, RT, 1024, 1) + 128 * i, 1);
                else wgmma_n40_0(e2[f & 1], da(f, i), make_desc(SB0 + OFF_WBI, RT, 1024, 1));
            }
            wgmma_commit();
        };
        auto mma_d = [&](int f, int i0, int i1) {
#pragma unroll
            for (int i = i0; i < i1; i++) wgmma_n128(ad, da(f, i), db(f, i), 1);
            wgmma_commit();
        };
#define ROWS_TO_ASYNC() asm volatile("fence.proxy.async::generic.acquire.sync_restrict::shared::cluster.cluster;" ::: "memory")
#define SYNC4() asm volatile("bar.sync 1, 128;" ::: "memory")
        uint32_t pk[8];
        static_for<0, 22>([&](auto KC) {
            constexpr int k = decltype(KC)::value;
            if (k > 1) {
                wgmma_wait<1>();
                if (l0) mbar_arrive(BAR(B_EMPTY + k - 2));
                cvt(pk, k - 2);
#pragma unroll
                for (int i = 64; i < 83; i++)
                    if (i != 81) asm volatile("mul.f32 %0, %0, 0f00000000;" : "+f"(acc[k & 1][i]));
            }
            if (k < 2 * NP || !(k & 1)) mbar_wait(BAR((k < 2 * NP && !(k & 1) ? B_F : B_PAIR) + k / 2), 0);
            mbar_wait(BAR(B_W + k), 0);
            ROWS_TO_ASYNC();
            if (k == 0) TS(19);
            wgmma_fence();
#pragma unroll
            for (int i = 0; i < 4; i++) wgmma_n168(acc[k & 1], da(k, i), db(k, i), k > 1 || i);
            wgmma_commit();
            if (k > 1) {
                SYNC4();
                store(pk, k - 2);
            }
        });
        {
            uint32_t p2[8], p3[8], p4[8];
            wgmma_wait<1>();
            if (l0) mbar_arrive(BAR(B_EMPTY + 20));
            cvt(pk, 20);
            mbar_wait(BAR(B_PAIR + 11), 0);
            mbar_wait(BAR(B_PAIR + 12), 0);
            mbar_wait(BAR(B_W + 22), 0);
            ROWS_TO_ASYNC();
            mma_e(22);
            SYNC4();
            store(pk, 20);
            wgmma_wait<1>();
            if (l0) mbar_arrive(BAR(B_EMPTY + 21));
            cvt(pk, 21);
#pragma unroll
            for (int i = 0; i < 64; i++) asm volatile("add.f32 %0, %1, %2;" : "=f"(ad[i]) : "f"(acc[0][i]), "f"(acc[1][i]));
            wgmma_fence();
            mma_d(22, 0, 1);
            mma_e(23);
            store(pk, 21);
            wgmma_wait<2>();
            cvt(p2, 22);
            mma_e(24);
            SYNC4();
            store(p2, 22);
            wgmma_wait<1>();
            cvt(p3, 23);
            mma_e(25);
            mma_d(22, 1, 3);
            store(p3, 23);
            wgmma_wait<1>();
            if (l0) mbar_arrive(BAR(B_ZRDY));
            TS(2);
            za[6] = za[7] = 0u;
            cvt(pk, 24);
            cvt(p4, 25);
#pragma unroll
            for (int i = 0; i < 6; i++) za[i] |= p4[7] & (ln >> 5);
            constexpr uint64_t d1 = make_desc(SB0 + OFF_SEF, 256, 128, 0), d2 = make_desc(SB0 + OFF_SEF + 1024, 512, 128, 0);
            float h[8], o[16];
#pragma unroll
            for (int i = 0; i < 16; i++) asm volatile("" : "=f"(o[i]), "=f"(h[i & 7]));
            wgmma_fence();
            wgmma_m64n16k16_rs<0>(h, za, d1);
            wgmma_m64n16k16_rs<1>(h, za + 4, d1 + 32);
            wgmma_commit();
            mma_d(22, 3, 4);
            mbar_wait(BAR(B_W + 23), 0);
            wgmma_fence();
            mma_d(23, 0, 4);
            wgmma_wait<2>();
            const uint32_t ha0 = pack_bf16(gelu2(h[0]), gelu2(h[1])), ha1 = pack_bf16(gelu2(h[2]), gelu2(h[3])), ha2 = pack_bf16(gelu2(h[4]), gelu2(h[5])),
                           ha3 = pack_bf16(gelu2(h[6]), gelu2(h[7]));
            wgmma_fence();
            wgmma_m64n32k16_rs<2>(o, ha0, ha1, ha2, ha3, d2);
            wgmma_commit();
            wgmma_wait<2>();
            if (l0) mbar_arrive(BAR(B_EMPTY + 22));
            mbar_wait(BAR(B_W + 24), 0);
            wgmma_fence();
            mma_d(24, 0, 4);
            wgmma_wait<1>();
            if (l0) mbar_arrive(BAR(B_EMPTY + 23));
            mbar_wait(BAR(B_W + 25), 0);
            wgmma_fence();
            mma_d(25, 0, 4);
            SYNC4();
            store(pk, 24);
            store(p4, 25);
#pragma unroll
            for (int i = 0; i < 2; i++) {
                uint32_t a[4];
#pragma unroll
                for (int k = 0; k < 4; k++) a[k] = pack_bf16(fmaf(tanh_fast(o[8 * i + 2 * k]), 0.5f, 0.5f), fmaf(tanh_fast(o[8 * i + 2 * k + 1]), 0.5f, 0.5f));
                sts128(sb + OFF_AP + i * 2048 + warp * 512 + ln * 16, a[0], a[1], a[2], a[3]);
            }
            __syncwarp();
            if (l0) mbar_arrive(BAR(B_EWRDY));
            wgmma_wait<1>();
            if (l0) mbar_arrive(BAR(B_EMPTY + 24));
            TS(3);
        }
        {
            wgmma_wait<0>();
            if (l0) mbar_arrive(BAR(B_EMPTY + 25));
            uint32_t hw[32];
#pragma unroll
            for (int i = 0; i < 32; i++) asm volatile("cvt.rn.bf16x2.f32 %0, %1, %2;" : "=r"(hw[i]) : "f"(ad[2 * i + 1]), "f"(ad[2 * i]));
            asm volatile("setmaxnreg.dec.sync.aligned.u32 %0;" ::"n"(R_DEEP2));
            TS(4);
            float o[4];
#pragma unroll
            for (int i = 0; i < 4; i++) asm volatile("" : "=f"(o[i]));
#pragma unroll
            for (int i = 0; i < 32; i++) hw[i] = gelu2p(hw[i]);
            wgmma_fence();
#pragma unroll
            for (int it = 0; it < 8; it++) wgmma_m64n8k16_rs(o, hw + 4 * it, make_desc(SB0 + OFF_W2, 16, 128, 0) + 2 * it, it);
            wgmma_commit();
            wgmma_wait<0>();
            o[2] = __shfl_sync(0xffffffffu, o[2], ln & 28);
            uint32_t da, db, tt;
            send_addr(sb, rank * 3, warp, da, db, tt);
            send_partial(da, db, tt, 0.5f * o[0], 0.5f * o[2]);
        }
        TS(5);
    } else {
        const int wgc = (warp >> 2) - 1, w4 = warp & 3;
        const char* so = (const char*)table + 16 * (lane & 7);
        auto rp = [&](uint32_t i) { return row_ptr(so, i); };
        const uint32_t d0 = opq(sb + OFF_RT + b * 128 + (((lane ^ b) & 7) << 4)), d1 = opq((d0 ^ 64) + 6 * RT);
        uint32_t c0;
        auto until = [&](int f) {
            for (;;) {
                uint32_t c;
                asm volatile("mov.u32 %0, %%clock;" : "=r"(c)::"memory");
                if (c - c0 >= f * 300) break;
                __nanosleep(32);
            }
        };
        {
            const int ia[4] = {i0a.x, i0a.y, i1a.x, i1a.y}, ib[4] = {i0b.x, i0b.y, i1b.x, i1b.y};
            static_for<0, NFIRST>([&](auto FC) {
                constexpr int f = decltype(FC)::value, o = (f >> 1) * RT;
                if (f) until(f);
                cp_async16(((f & 1) ? d1 : d0) + o, rp(ia[f]));
                cp_async16(((f & 1) ? d1 : d0) + o + 4096, rp(ib[f]));
                cp_async_mbar_arrive_noinc(BAR(((f & 1) ? B_PAIR : B_F) + (f >> 1)));
                if (f == 0) asm volatile("mov.u32 %0, %%clock;" : "=r"(c0)::"memory");
            });
            if (wgc == 0) TS(6);
        }
        asm volatile("setmaxnreg.inc.sync.aligned.u32 %0;" ::"n"(R_CR1));
        uint32_t M[8][12], y[4][2];
        {
            const uint32_t pa = opq(sb + OFF_RT + (t & 1) * 6 * RT + (16 * w4 + g) * 128 + (((4 * rank + 2 * wgc) ^ g ^ (4 * (t & 1))) << 4)), t1 = opq(t >> 1);
            const uint32_t ia = opq(sb + OFF_IDX + b * NF * 4);
#pragma unroll
            for (int i = 0; i < 96; i++) asm volatile("" : "=r"(M[i / 12][i % 12]));
            mbar_wait(BAR(B_IDX), 0);
            uint32_t x[13][4];
#pragma unroll
            for (int p = 2; p < 13; p++)
                asm volatile("ld.shared.v2.u32 {%0,%1}, [%4];\nld.shared.v2.u32 {%2,%3}, [%4 + 3328];" : "=r"(x[p][0]), "=r"(x[p][2]), "=r"(x[p][1]), "=r"(x[p][3]) : "r"(ia + p * 8));
            const uint32_t pb = opq(pa ^ 16);
            auto conv = [&](int G) {
#pragma unroll
                for (int i = 0; i < 16; i++) {
                    uint32_t &u = M[i >> 1][4 * G + 2 * (i & 1)], &v = M[i >> 1][4 * G + 2 * (i & 1) + 1];
                    asm volatile("{\n.reg .b32 t;\nprmt.b32 t, %0, %1, 0x5410;\nprmt.b32 %1, %0, %1, 0x7632;\nmov.b32 %0, t;\n}\n" : "+r"(u), "+r"(v));
                }
#pragma unroll
                for (int i = 0; i < 8; i++)
                    asm volatile("{\n.reg .pred p;\nsetp.eq.u32 p, %5, 2;\n@p st.shared.v4.u32 [%4], {%0,%1,%2,%3};\n}\n" ::"r"(M[i & 4][4 * G + (i & 3)]), "r"(M[(i & 4) + 1][4 * G + (i & 3)]),
                                 "r"(M[(i & 4) + 2][4 * G + (i & 3)]), "r"(M[(i & 4) + 3][4 * G + (i & 3)]), "r"(pa), "r"(t1));
            };
            auto gather = [&](auto PC) {
                constexpr int p = decltype(PC)::value;
                constexpr uint32_t o1 = (tile(2 * p + 1) - 6) * RT;
                if (p < 6) until(2 * p);
                cp_async16(d0 + tile(2 * p) * RT, rp(x[p][0]));
                cp_async16(d0 + tile(2 * p) * RT + 4096, rp(x[p][1]));
                if (p < NP) cp_async_mbar_arrive_noinc(BAR(B_F + p));
                if (p < 6) until(2 * p + 1);
                cp_async16(d1 + o1, rp(x[p][2]));
                cp_async16(d1 + o1 + 4096, rp(x[p][3]));
                cp_async_mbar_arrive_noinc(BAR(B_PAIR + p));
            };
            auto pick = [&](auto QC) {
                constexpr int q = decltype(QC)::value, c = 4 * (q >> 2) + ((q >> 1) & 1);
#pragma unroll
                for (int i = 0; i < 4; i++)
                    asm volatile("{\n.reg .pred p;\nsetp.eq.u32 p, %5, %6;\n@p ld.shared.v4.u32 {%0,%1,%2,%3}, [%4];\n}\n"
                                 : "+r"(M[2 * (i & 2)][c + 2 * (i & 1)]), "+r"(M[2 * (i & 2) + 1][c + 2 * (i & 1)]), "+r"(M[2 * (i & 2) + 2][c + 2 * (i & 1)]),
                                   "+r"(M[2 * (i & 2) + 3][c + 2 * (i & 1)])
                                 : "r"(((i & 2) ? pb : pa) + tile(2 * q) * RT + (i & 1) * 1024 + (tile(2 * q + 1) - 6 - tile(2 * q)) * (t & 1) * RT), "r"(t1), "n"(q & 1));
                __syncwarp();
                if (elect_one()) mbar_arrive(BAR(B_W + 2 * q + 2));
                if (q == 4 || q == 8) conv(q / 4 - 1);
            };
#define IC(x) std::integral_constant<int, x>{}
            gather(IC(2));
            gather(IC(3));
            static_for<0, 3>([&](auto QC) {
                constexpr int q = decltype(QC)::value;
                mbar_wait(BAR(B_PAIR + q), 0);
                pick(QC);
                if constexpr (q < 2) gather(IC(q + 4));
            });
            static_for<3, 12>([&](auto QC) {
                constexpr int q = decltype(QC)::value, p = q < 7 ? q + 3 : q == 8 ? 10 : q == 11 ? 12 : 0;
                if (q == 10) {
                    mbar_wait(BAR(B_EMPTY + 14), 0);
                    gather(IC(11));
                }
                mbar_wait(BAR(B_EMPTY + 2 * q - 5 - (q == 11)), 0);
                if constexpr (p == 12) gather(IC(12));
                mbar_wait(BAR(B_PAIR + q), 0);
                if constexpr (p && p < 12) gather(IC(p));
                if (q == 9) {
#pragma unroll
                    for (int i = 0; i < 4; i++) asm volatile("prefetch.global.L2 [%0];" ::"l"(rp(rank ? x[11 + (i >> 1)][2 * (i & 1) + 1] : x[11 + (i >> 1)][2 * (i & 1)])));
                }
                pick(QC);
            });
            const uint32_t ta = sb + OFF_RT + tile(24) * RT + (16 * w4 + g) * 128 + (((4 * rank + 2 * wgc + (t >> 1)) ^ g) << 4) + 8 * (t & 1);
            mbar_wait(BAR(B_PAIR + 12), 0);
#pragma unroll
            for (int k = 0; k < 4; k++) asm volatile("ld.shared.v2.u32 {%0,%1}, [%2];" : "=r"(y[k][0]), "=r"(y[k][1]) : "r"(((k & 1) ? (ta ^ 64) - (tile(24) - tile(25)) * RT : ta) + (k >> 1) * 1024));
            __syncwarp();
            if (elect_one()) mbar_arrive(BAR(B_W + 25));
            conv(2);
        }
        uint32_t TL[4][2];
        uint32_t ap[8], a0, a1;
        uint32_t A0[8], A1[8], Aq[8], w[8], aq;
        {
            const int r = lane & 7, bh = (lane >> 3) & 1, ig = lane >> 4;
            const uint32_t x = sb + OFF_EW + wgc * 256 + (2 * w4 + bh) * 512 + (8 * ig + 4 * (r & 1) + (r >> 1)) * EWP;
            a0 = opq(x);
            a1 = opq(x + (!ig || r == 0 ? 16 : r == 1 ? 13 : r == 2 ? 11 : 8) * EWP);
            aq = opq(sb + OFF_AP + w4 * 512 + lane * 16);
        }
        asm volatile("barrier.cluster.wait.acquire.aligned;" ::: "memory");
        mbar_wait(BAR(B_CFULL), 0);
        mbar_wait(BAR(B_EWRDY), 0);
        u_lda(A0, a0, a1);
#pragma unroll
        for (int i = 0; i < 2; i++) {
            const uint4 v = lds128(aq + i * 2048);
            ap[4 * i] = v.x, ap[4 * i + 1] = v.y, ap[4 * i + 2] = v.z, ap[4 * i + 3] = v.w;
        }
        if (wgc == 0) TS(60);
        asm volatile("setmaxnreg.inc.sync.aligned.u32 %0;" ::"n"(R_CR2));
        if (wgc == 0) TS(61);
        asm volatile("mov.u32 %0, %%clock;\nand.b32 %0, %0, %1;" : "=r"(aq) : "r"(warp >> 4));
        a0 |= aq, a1 |= aq;
#pragma unroll
        for (int k = 0; k < 8; k++) {
            TL[k >> 1][k & 1] = __byte_perm(y[2 * (k & 1)][k >> 2], y[2 * (k & 1) + 1][k >> 2], (0x5410 + 0x2222 * ((k >> 1) & 1)) | aq);
            ap[k] |= aq, A0[k] |= aq & TL[k >> 1][k & 1];
        }
        constexpr uint64_t dt = make_desc(SB0 + OFF_RT + 13 * RT, 512, 128, 0), dqc = make_desc(SB0 + OFF_ID, 128, 128, 0);
        const uint64_t dq = uni64(dqc + (sb >> 28));
        auto dsc = [&](int e, int pq) {
            const int s0 = (int)(CPOS >> (8 * (e >> 1))) & 15, s1 = (int)(CPOS >> (8 * (e >> 1) + 4)) & 15;
            return dt + (s0 + wgc * (s1 - s0)) * (CHUNK >> 4) + ((e & 1) * 2 + pq) * (TILE >> 4);
        };
        float S[4], accP[16], accQ[16];
#pragma unroll
        for (int i = 0; i < 16; i++) asm volatile("" : "=f"(accP[i]), "=f"(accQ[i]));
        u_lda(A1, a0 + 16, a1 + 16);
#pragma unroll
        for (int i = 0; i < 4; i++) asm volatile("" : "=f"(S[i]));
#pragma unroll
        for (int k = 0; k < 8; k++) Aq[k] = hmul2_bf16(A0[k], ap[k]);
        wgmma_fence();
        u_mma(accP, A0, dsc(0, 0));
        wgmma_commit();
        u_mma(accQ, Aq, dsc(0, 1));
        wgmma_commit();
        if (wgc == 0) TS(62);
        auto pack8 = [&](uint32_t (&d)[8], const float (&a)[16]) {
#pragma unroll
            for (int k = 0; k < 8; k++) asm volatile("cvt.rn.bf16x2.f32 %0, %1, %2;" : "=r"(d[k]) : "f"(a[2 * k + 1]), "f"(a[2 * k]));
        };
        uint32_t da, db, tt;
        static_for<0, 8>([&](auto PC) {
            constexpr int p = decltype(PC)::value, e = 2 * p;
            if (p == 7) send_addr(sb, rank * 3 + 1 + wgc, w4, da, db, tt);
            auto mw = [&](int s, int k) { return k < 6 ? M[p][2 * k + s] : TL[(e + s) & 3][k - 6]; };
            uint32_t tp[8], tq[8];
            wgmma_wait<1>();
            pack8(tp, accP);
            wgmma_fence();
            u_mma(accP, A1, dsc(e + 1, 0));
            if (p) {
                wgmma_m64n8k16_rs(S, w, dq, p > 1);
                wgmma_m64n8k16_rs(S, w + 4, dq, 1);
            }
            wgmma_commit();
            if (p < 7) u_lda(A0, a0 + 16 * e + 32, a1 + 16 * e + 32);
            wgmma_wait<1>();
            pack8(tq, accQ);
#pragma unroll
            for (int k = 0; k < 8; k++) Aq[k] = hmul2_bf16(A1[k], ap[k]);
            wgmma_fence();
            u_mma(accQ, Aq, dsc(e + 1, 1));
            wgmma_commit();
#pragma unroll
            for (int k = 0; k < 8; k++) tq[k] = hfma2_bf16(tq[k], ap[k], tp[k]);
            if (p == 0 || p == 2 || p == 5) mbar_wait(BAR(B_CFULL + 1 + p / 2), 0);
            wgmma_wait<1>();
            pack8(tp, accP);
            if (p < 7) {
                wgmma_fence();
                u_mma(accP, A0, dsc(e + 2, 0));
                wgmma_commit();
                u_lda(A1, a0 + 16 * e + 48, a1 + 16 * e + 48);
            }
#pragma unroll
            for (int k = 0; k < 8; k++) w[k] = hmul2_bf16(tq[k], mw(0, k));
            wgmma_wait<(p < 7)>();
            if (p == 0 && elect_one()) mbar_arrive(BAR(B_CDONE));
            pack8(tq, accQ);
            if (p < 7) {
#pragma unroll
                for (int k = 0; k < 8; k++) Aq[k] = hmul2_bf16(A0[k], ap[k]);
                wgmma_fence();
                u_mma(accQ, Aq, dsc(e + 2, 1));
                wgmma_commit();
            }
#pragma unroll
            for (int k = 0; k < 8; k++) w[k] = hfma2_bf16(hfma2_bf16(tq[k], ap[k], tp[k]), mw(1, k), w[k]);
        });
        wgmma_fence();
        wgmma_m64n8k16_rs(S, w, dq, 1);
        wgmma_m64n8k16_rs(S, w + 4, dq, 1);
        wgmma_commit();
        wgmma_wait<0>();
        send_partial(da, db, tt, S[0], S[2]);
        if (wgc == 0) TS(14);
    }
#undef BAR
}

typedef CUresult (*PFN_encodeTiled)(CUtensorMap*, CUtensorMapDataType, cuuint32_t, void*, const cuuint64_t*, const cuuint64_t*,
                                    const cuuint32_t*, const cuuint32_t*, CUtensorMapInterleave, CUtensorMapSwizzle,
                                    CUtensorMapL2promotion, CUtensorMapFloatOOBfill);

}

extern "C" void kernel_launch(void* const* d_in, const int* in_sizes, int n_in, void* d_out, int out_size) {
    const int* idx = (const int*)d_in[0];
    const __nv_bfloat16* table = (const __nv_bfloat16*)d_in[1];
    const __nv_bfloat16* se_w1 = (const __nv_bfloat16*)d_in[2];
    const __nv_bfloat16* se_w2 = (const __nv_bfloat16*)d_in[3];
    const __nv_bfloat16* w_bi = (const __nv_bfloat16*)d_in[4];
    const __nv_bfloat16* w_cross = (const __nv_bfloat16*)d_in[5];
    const __nv_bfloat16* w_deep1 = (const __nv_bfloat16*)d_in[6];
    const __nv_bfloat16* w_deep2 = (const __nv_bfloat16*)d_in[7];
    __nv_bfloat16* out = (__nv_bfloat16*)d_out;

    static PFN_encodeTiled enc = nullptr;
    if (!enc) {
        void* fn = nullptr;
        cudaDriverEntryPointQueryResult qres;
        cudaGetDriverEntryPoint("cuTensorMapEncodeTiled", &fn, cudaEnableDefault, &qres);
        enc = (PFN_encodeTiled)fn;
        cudaFuncSetAttribute(fused_kernel, cudaFuncAttributeMaxDynamicSharedMemorySize, SMEM);
    }
    CUtensorMap tm;
    {
        cuuint64_t gdim[3] = {64, (cuuint64_t)(NF * ND), 4};
        cuuint64_t gstr[2] = {(cuuint64_t)NH * 2, 128};
        cuuint32_t box[3] = {64, 64, 1};
        cuuint32_t estr[3] = {1, 1, 1};
        enc(&tm, CU_TENSOR_MAP_DATA_TYPE_BFLOAT16, 3, (void*)w_deep1, gdim, gstr, box, estr, CU_TENSOR_MAP_INTERLEAVE_NONE,
            CU_TENSOR_MAP_SWIZZLE_128B, CU_TENSOR_MAP_L2_PROMOTION_L2_256B, CU_TENSOR_MAP_FLOAT_OOB_FILL_NONE);
    }
    fused_kernel<<<128, 512, SMEM>>>(idx, table, w_deep1, w_bi, w_deep2, w_cross, se_w1, se_w2, out, tm);
}
```

```cpp
#include <cuda_runtime.h>
#include <cuda_bf16.h>
#include <cuda.h>
#include <stdint.h>
#include <type_traits>
#include <utility>

#define R_DEEP 216
#define R_CR1 136
#define R_CR2 208
#define R_DEEP2 72
#define R_PROD 24

namespace {

constexpr int NF = 26, ND = 64, NH = 256, NFR = 13;

#define TS(slot)
#define TSL(slot)

__device__ __forceinline__ uint32_t smem_u32(const void* p) { return (uint32_t)__cvta_generic_to_shared(p); }
__device__ __forceinline__ void mbar_init(uint32_t bar, uint32_t cnt) {
    asm volatile("mbarrier.init.shared::cta.b64 [%0], %1;" ::"r"(bar), "r"(cnt));
}
__device__ __forceinline__ void mbar_expect_tx(uint32_t bar, uint32_t bytes) {
    asm volatile("mbarrier.arrive.expect_tx.shared::cta.b64 _, [%0], %1;" ::"r"(bar), "r"(bytes) : "memory");
}
__device__ __forceinline__ void mbar_arrive(uint32_t bar) {
    asm volatile("mbarrier.arrive.shared::cta.b64 _, [%0];" ::"r"(bar) : "memory");
}
__device__ __forceinline__ void mbar_wait(uint32_t bar, uint32_t parity) {
    asm volatile(
        "{\n"
        ".reg .pred p;\n"
        "WAIT_%=:\n"
        "mbarrier.try_wait.parity.shared::cta.b64 p, [%0], %1;\n"
        "@p bra.uni DONE_%=;\nbra.uni WAIT_%=;\nDONE_%=:\n"
        "}\n" ::"r"(bar),
        "r"(parity)
        : "memory");
}
__device__ __forceinline__ uint32_t opq(uint32_t x) { return __shfl_xor_sync(0xffffffffu, x, 0); }
__device__ __forceinline__ uint64_t uni64(uint64_t x) {
    uint32_t lo = (uint32_t)x, hi = (uint32_t)(x >> 32);
    asm volatile("shfl.sync.idx.b32 %0, %0, 0, 31, -1;\nshfl.sync.idx.b32 %1, %1, 0, 31, -1;" : "+r"(lo), "+r"(hi));
    return ((uint64_t)hi << 32) | lo;
}
__device__ __forceinline__ bool elect_one() {
    uint32_t r;
    asm volatile("{\n.reg .pred p;\nelect.sync _|p, 0xffffffff;\nselp.u32 %0, 1, 0, p;\n}\n" : "=r"(r));
    return r;
}
__device__ __forceinline__ const void* row_ptr(const void* base, uint32_t i) {
    const void* r;
    asm("mad.wide.u32 %0, %1, 128, %2;" : "=l"(r) : "r"(i), "l"(base));
    return r;
}
__device__ __forceinline__ void mbar_wait_bounded(uint32_t bar, uint32_t parity) {
    asm volatile(
        "{\n"
        ".reg .pred p;\n"
        ".reg .u32 c;\n"
        "mov.u32 c, 0;\n"
        "WAIT_%=:\n"
        "mbarrier.try_wait.parity.shared::cta.b64 p, [%0], %1;\n"
        "@p bra.uni DONE_%=;\n"
        "add.u32 c, c, 1;\n"
        "setp.lt.u32 p, c, 0x400000;\n"
        "@p bra.uni WAIT_%=;\n"
        "trap;\n"
        "DONE_%=:\n"
        "}\n" ::"r"(bar),
        "r"(parity)
        : "memory");
}
__device__ __forceinline__ void cp_async16(uint32_t dst, const void* src) {
    asm volatile("cp.async.cg.shared.global [%0], [%1], 16;" ::"r"(dst), "l"(src) : "memory");
}
__device__ __forceinline__ void cp_async_mbar_arrive_noinc(uint32_t bar) {
    asm volatile("cp.async.mbarrier.arrive.noinc.shared::cta.b64 [%0];" ::"r"(bar) : "memory");
}
__device__ __forceinline__ void tma_load_3d(uint32_t dst, const void* tmap, int c0, int c1, int c2, uint32_t bar) {
    asm volatile(
        "cp.async.bulk.tensor.3d.shared::cluster.global.mbarrier::complete_tx::bytes [%0], [%1, {%3, %4, %5}], [%2];" ::"r"(dst),
        "l"(tmap), "r"(bar), "r"(c0), "r"(c1), "r"(c2)
        : "memory");
}
__device__ __forceinline__ void bulk_load(uint32_t dst, const void* src, uint32_t bytes, uint32_t bar) {
    asm volatile("cp.async.bulk.shared::cluster.global.mbarrier::complete_tx::bytes [%0], [%1], %2, [%3];" ::"r"(dst), "l"(src), "r"(bytes),
                 "r"(bar)
                 : "memory");
}
__device__ __forceinline__ void fence_proxy_async() { asm volatile("fence.proxy.async.shared::cta;" ::: "memory"); }
__device__ __forceinline__ void wgmma_fence() { asm volatile("wgmma.fence.sync.aligned;" ::: "memory"); }
__device__ __forceinline__ void wgmma_commit() { asm volatile("wgmma.commit_group.sync.aligned;" ::: "memory"); }
template <int N> __device__ __forceinline__ void wgmma_wait() { asm volatile("wgmma.wait_group.sync.aligned %0;" ::"n"(N) : "memory"); }

__device__ __forceinline__ void ldsm_x4_t(uint32_t addr, uint32_t& r0, uint32_t& r1, uint32_t& r2, uint32_t& r3) {
    asm volatile("ldmatrix.sync.aligned.m8n8.x4.trans.shared.b16 {%0,%1,%2,%3}, [%4];" : "=r"(r0), "=r"(r1), "=r"(r2), "=r"(r3) : "r"(addr));
}
__device__ __forceinline__ void stsm_x4_t(uint32_t addr, uint32_t r0, uint32_t r1, uint32_t r2, uint32_t r3) {
    asm volatile("stmatrix.sync.aligned.m8n8.x4.trans.shared.b16 [%0], {%1,%2,%3,%4};" ::"r"(addr), "r"(r0), "r"(r1), "r"(r2), "r"(r3) : "memory");
}
__device__ __forceinline__ uint4 lds128(uint32_t addr) {
    uint4 v;
    asm volatile("ld.shared.v4.u32 {%0,%1,%2,%3}, [%4];" : "=r"(v.x), "=r"(v.y), "=r"(v.z), "=r"(v.w) : "r"(addr));
    return v;
}
__device__ __forceinline__ uint32_t lds32(uint32_t addr) {
    uint32_t v;
    asm volatile("ld.shared.u32 %0, [%1];" : "=r"(v) : "r"(addr));
    return v;
}
__device__ __forceinline__ void sts128(uint32_t addr, uint32_t a, uint32_t b, uint32_t c, uint32_t d) {
    asm volatile("st.shared.v4.u32 [%0], {%1,%2,%3,%4};" ::"r"(addr), "r"(a), "r"(b), "r"(c), "r"(d) : "memory");
}
__device__ __forceinline__ uint32_t pack_bf16(float lo, float hi) {
    uint32_t r;
    asm("cvt.rn.bf16x2.f32 %0, %1, %2;" : "=r"(r) : "f"(hi), "f"(lo));
    return r;
}
__device__ __forceinline__ uint32_t hmul2_bf16(uint32_t a, uint32_t b) {
    uint32_t r;
    asm("mul.rn.bf16x2 %0, %1, %2;" : "=r"(r) : "r"(a), "r"(b));
    return r;
}
__device__ __forceinline__ float tanh_fast(float x) {
    float r;
    asm("tanh.approx.f32 %0, %1;" : "=f"(r) : "f"(x));
    return r;
}
#define WG_ACC8(c, b) c(acc[b]), c(acc[b + 1]), c(acc[b + 2]), c(acc[b + 3]), c(acc[b + 4]), c(acc[b + 5]), c(acc[b + 6]), c(acc[b + 7])
__device__ __forceinline__ void wgmma_n168(float (&acc)[84], uint64_t da, uint64_t db, int sc) {
    asm volatile("{\n.reg .pred p;\nsetp.ne.b32 p, %86, 0;\nwgmma.mma_async.sync.aligned.m64n168k16.f32.bf16.bf16 {%0,%1,%2,%3,%4,%5,%6,%7,%8,%9,%10,%11,%12,%13,%14,%15,%16,%17,%18,%19,%20,%21,%22,%23,%24,%25,%26,%27,%28,%29,%30,%31,%32,%33,%34,%35,%36,%37,%38,%39,%40,%41,%42,%43,%44,%45,%46,%47,%48,%49,%50,%51,%52,%53,%54,%55,%56,%57,%58,%59,%60,%61,%62,%63,%64,%65,%66,%67,%68,%69,%70,%71,%72,%73,%74,%75,%76,%77,%78,%79,%80,%81,%82,%83}, %84, %85, p, 1, 1, 0, 1;\n}\n"
                 : "+f"(acc[0]), "+f"(acc[1]), "+f"(acc[2]), "+f"(acc[3]), "+f"(acc[4]), "+f"(acc[5]), "+f"(acc[6]), "+f"(acc[7]), "+f"(acc[8]), "+f"(acc[9]), "+f"(acc[10]), "+f"(acc[11]), "+f"(acc[12]), "+f"(acc[13]), "+f"(acc[14]), "+f"(acc[15]), "+f"(acc[16]), "+f"(acc[17]), "+f"(acc[18]), "+f"(acc[19]), "+f"(acc[20]), "+f"(acc[21]), "+f"(acc[22]), "+f"(acc[23]), "+f"(acc[24]), "+f"(acc[25]), "+f"(acc[26]), "+f"(acc[27]), "+f"(acc[28]), "+f"(acc[29]), "+f"(acc[30]), "+f"(acc[31]), "+f"(acc[32]), "+f"(acc[33]), "+f"(acc[34]), "+f"(acc[35]), "+f"(acc[36]), "+f"(acc[37]), "+f"(acc[38]), "+f"(acc[39]), "+f"(acc[40]), "+f"(acc[41]), "+f"(acc[42]), "+f"(acc[43]), "+f"(acc[44]), "+f"(acc[45]), "+f"(acc[46]), "+f"(acc[47]), "+f"(acc[48]), "+f"(acc[49]), "+f"(acc[50]), "+f"(acc[51]), "+f"(acc[52]), "+f"(acc[53]), "+f"(acc[54]), "+f"(acc[55]), "+f"(acc[56]), "+f"(acc[57]), "+f"(acc[58]), "+f"(acc[59]), "+f"(acc[60]), "+f"(acc[61]), "+f"(acc[62]), "+f"(acc[63]), "+f"(acc[64]), "+f"(acc[65]), "+f"(acc[66]), "+f"(acc[67]), "+f"(acc[68]), "+f"(acc[69]), "+f"(acc[70]), "+f"(acc[71]), "+f"(acc[72]), "+f"(acc[73]), "+f"(acc[74]), "+f"(acc[75]), "+f"(acc[76]), "+f"(acc[77]), "+f"(acc[78]), "+f"(acc[79]), "+f"(acc[80]), "+f"(acc[81]), "+f"(acc[82]), "+f"(acc[83])
                 : "l"(da), "l"(db), "r"(sc));
}
__device__ __forceinline__ void wgmma_n128(float (&acc)[64], uint64_t da, uint64_t db, int sc) {
    asm volatile("{\n.reg .pred p;\nsetp.ne.b32 p, %66, 0;\nwgmma.mma_async.sync.aligned.m64n128k16.f32.bf16.bf16 {%0,%1,%2,%3,%4,%5,%6,%7,%8,%9,%10,%11,%12,%13,%14,%15,%16,%17,%18,%19,%20,%21,%22,%23,%24,%25,%26,%27,%28,%29,%30,%31,%32,%33,%34,%35,%36,%37,%38,%39,%40,%41,%42,%43,%44,%45,%46,%47,%48,%49,%50,%51,%52,%53,%54,%55,%56,%57,%58,%59,%60,%61,%62,%63}, %64, %65, p, 1, 1, 0, 1;\n}\n"
                 : "+f"(acc[0]), "+f"(acc[1]), "+f"(acc[2]), "+f"(acc[3]), "+f"(acc[4]), "+f"(acc[5]), "+f"(acc[6]), "+f"(acc[7]), "+f"(acc[8]), "+f"(acc[9]), "+f"(acc[10]), "+f"(acc[11]), "+f"(acc[12]), "+f"(acc[13]), "+f"(acc[14]), "+f"(acc[15]), "+f"(acc[16]), "+f"(acc[17]), "+f"(acc[18]), "+f"(acc[19]), "+f"(acc[20]), "+f"(acc[21]), "+f"(acc[22]), "+f"(acc[23]), "+f"(acc[24]), "+f"(acc[25]), "+f"(acc[26]), "+f"(acc[27]), "+f"(acc[28]), "+f"(acc[29]), "+f"(acc[30]), "+f"(acc[31]), "+f"(acc[32]), "+f"(acc[33]), "+f"(acc[34]), "+f"(acc[35]), "+f"(acc[36]), "+f"(acc[37]), "+f"(acc[38]), "+f"(acc[39]), "+f"(acc[40]), "+f"(acc[41]), "+f"(acc[42]), "+f"(acc[43]), "+f"(acc[44]), "+f"(acc[45]), "+f"(acc[46]), "+f"(acc[47]), "+f"(acc[48]), "+f"(acc[49]), "+f"(acc[50]), "+f"(acc[51]), "+f"(acc[52]), "+f"(acc[53]), "+f"(acc[54]), "+f"(acc[55]), "+f"(acc[56]), "+f"(acc[57]), "+f"(acc[58]), "+f"(acc[59]), "+f"(acc[60]), "+f"(acc[61]), "+f"(acc[62]), "+f"(acc[63])
                 : "l"(da), "l"(db), "r"(sc));
}
__device__ __forceinline__ void wgmma_n40(float (&acc)[20], uint64_t da, uint64_t db, int sc) {
    asm volatile("{\n.reg .pred p;\nsetp.ne.b32 p, %22, 0;\nwgmma.mma_async.sync.aligned.m64n40k16.f32.bf16.bf16 {%0,%1,%2,%3,%4,%5,%6,%7,%8,%9,%10,%11,%12,%13,%14,%15,%16,%17,%18,%19}, %20, %21, p, 1, 1, 0, 1;\n}\n"
                 : "+f"(acc[0]), "+f"(acc[1]), "+f"(acc[2]), "+f"(acc[3]), "+f"(acc[4]), "+f"(acc[5]), "+f"(acc[6]), "+f"(acc[7]), "+f"(acc[8]), "+f"(acc[9]), "+f"(acc[10]), "+f"(acc[11]), "+f"(acc[12]), "+f"(acc[13]), "+f"(acc[14]), "+f"(acc[15]), "+f"(acc[16]), "+f"(acc[17]), "+f"(acc[18]), "+f"(acc[19])
                 : "l"(da), "l"(db), "r"(sc));
}
__device__ __forceinline__ void wgmma_n40_0(float (&acc)[20], uint64_t da, uint64_t db) {
    asm volatile("{\n.reg .pred p;\nsetp.ne.b32 p, 0, 0;\nwgmma.mma_async.sync.aligned.m64n40k16.f32.bf16.bf16 {%0,%1,%2,%3,%4,%5,%6,%7,%8,%9,%10,%11,%12,%13,%14,%15,%16,%17,%18,%19}, %20, %21, p, 1, 1, 0, 1;\n}\n"
                 : "=f"(acc[0]), "=f"(acc[1]), "=f"(acc[2]), "=f"(acc[3]), "=f"(acc[4]), "=f"(acc[5]), "=f"(acc[6]), "=f"(acc[7]), "=f"(acc[8]), "=f"(acc[9]), "=f"(acc[10]), "=f"(acc[11]), "=f"(acc[12]), "=f"(acc[13]), "=f"(acc[14]), "=f"(acc[15]), "=f"(acc[16]), "=f"(acc[17]), "=f"(acc[18]), "=f"(acc[19])
                 : "l"(da), "l"(db));
}
#define WG_N32(c, sc)                                                   \
    asm volatile(                                                       \
        "{\n"                                                           \
        ".reg .pred p;\n"           \
        "setp.ne.b32 p, " sc ", 0;\n"                                   \
        "wgmma.mma_async.sync.aligned.m64n32k16.f32.bf16.bf16 "         \
        "{%0,%1,%2,%3,%4,%5,%6,%7,%8,%9,%10,%11,%12,%13,%14,%15},"      \
        " {%16,%17,%18,%19}, %20, p, 1, 1, 0;\n"                        \
        "}\n"                                                           \
        : WG_ACC8(c, 0), WG_ACC8(c, 8)                                  \
        : "r"(a0), "r"(a1), "r"(a2), "r"(a3), "l"(db))
template <int SC>
__device__ __forceinline__ void wgmma_m64n32k16_rs(float (&acc)[16], uint32_t a0, uint32_t a1, uint32_t a2, uint32_t a3, uint64_t db) {
    if constexpr (SC == 1) WG_N32("+f", "1");
    else if constexpr (SC == 2) WG_N32("+f", "0");
    else WG_N32("=f", "0");
}

__host__ __device__ constexpr uint64_t make_desc(uint32_t addr, uint32_t lbo_bytes, uint32_t sbo_bytes, uint32_t swz) {
    uint64_t d = 0;
    d |= (uint64_t)((addr & 0x3FFFF) >> 4);
    d |= (uint64_t)((lbo_bytes >> 4) & 0x3FFF) << 16;
    d |= (uint64_t)((sbo_bytes >> 4) & 0x3FFF) << 32;
    d |= (uint64_t)swz << 62;
    return d;
}
__device__ __forceinline__ uint32_t ldg_u16(const __nv_bfloat16* p) { return (uint32_t)__ldg(reinterpret_cast<const unsigned short*>(p)); }
template <int N, class F, int... I>
__device__ __forceinline__ void static_for_impl(F&& f, std::integer_sequence<int, I...>) {
    (f(std::integral_constant<int, N + I>{}), ...);
}
template <int B, int E, class F>
__device__ __forceinline__ void static_for(F&& f) {
    static_for_impl<B>(f, std::make_integer_sequence<int, E - B>{});
}

__device__ __forceinline__ uint32_t hfma2_bf16(uint32_t a, uint32_t b, uint32_t c) {
    uint32_t r;
    asm("fma.rn.bf16x2 %0, %1, %2, %3;" : "=r"(r) : "r"(a), "r"(b), "r"(c));
    return r;
}
__device__ __forceinline__ float gelu2(float x) {
    const float k0 = 0.7978845608028654f, k01 = 0.7978845608028654f * 0.044715f;
    return fmaf(x, tanh_fast(x * fmaf(x * x, k01, k0)), x);
}
__device__ __forceinline__ uint32_t gelu2p(uint32_t x) {
    uint32_t t;
    const uint32_t u = hmul2_bf16(x, hfma2_bf16(hmul2_bf16(x, x), 0x3D123D12u, 0x3F4C3F4Cu));
    asm("tanh.approx.bf16x2 %0, %1;" : "=r"(t) : "r"(u));
    return hfma2_bf16(x, t, x);
}
__device__ __forceinline__ void wgmma_m64n8k16_rs(float (&acc)[4], const uint32_t* a, uint64_t db, int sc) {
    asm volatile("{\n.reg .pred p;\nsetp.ne.b32 p, %9, 0;\nwgmma.mma_async.sync.aligned.m64n8k16.f32.bf16.bf16 {%0,%1,%2,%3}, {%4,%5,%6,%7}, %8, p, 1, 1, 0;\n}\n"
                 : "+f"(acc[0]), "+f"(acc[1]), "+f"(acc[2]), "+f"(acc[3])
                 : "r"(a[0]), "r"(a[1]), "r"(a[2]), "r"(a[3]), "l"(db), "r"(sc));
}

template <int SC>
__device__ __forceinline__ void wgmma_m64n16k16_rs(float (&acc)[8], const uint32_t* a, uint64_t db) {
    asm volatile("{\n.reg .pred p;\nsetp.ne.b32 p, %13, 0;\nwgmma.mma_async.sync.aligned.m64n16k16.f32.bf16.bf16 {%0,%1,%2,%3,%4,%5,%6,%7}, {%8,%9,%10,%11}, %12, p, 1, 1, 0;\n}\n"
                 : WG_ACC8("+f", 0)
                 : "r"(a[0]), "r"(a[1]), "r"(a[2]), "r"(a[3]), "l"(db), "n"(SC));
}

constexpr int SB0 = 1024;
constexpr int SLOT = 4096;
constexpr int EWP = SLOT + 16;
constexpr int OFF_EW = 608;
constexpr int OFF_RT = 1024;
constexpr int RT = 8192;
__host__ __device__ constexpr int tile(int f) { return f == 13 ? 17 : f < 21 ? (f + 11 * (f & 1)) / 2 : (f & 1) ? (f + 1) / 2 : f - 5; }
__host__ __device__ constexpr int w1_dist(int f) { return f < 16 ? (int)(0x5713457134571345ull >> (4 * f)) & 7 : (0x5134 >> (4 * (f & 3))) & 7; }
constexpr int HS_BYTES = 16384;
constexpr int OFF_WBI = OFF_RT + 26 * RT;
constexpr int OFF_IDX = OFF_RT + 15 * RT;
constexpr int OFF_SEF = OFF_WBI + RT;
constexpr int OFF_AP = OFF_SEF + 2048;
constexpr int OFF_W2 = 0;
constexpr int OFF_DP = OFF_AP + 4096;
constexpr int OFF_ID = OFF_DP + 6 * 32 * 4;
constexpr int OFF_BAR = OFF_ID + 256;
constexpr int TILE = 2048;
constexpr int CHUNK = 4 * TILE;
constexpr int NCHUNK = 16;
constexpr uint64_t CPOS = 0x21A70D986543CB21ull;
static_assert(OFF_EW + 25 * EWP + SLOT <= OFF_RT + 13 * RT && CHUNK == RT, "layout");
static_assert(OFF_ID % 128 == 0, "align");
constexpr int B_CFULL = 0,
              B_F = 4,
              B_W = 16,
              B_EMPTY = 48, B_ZRDY = B_EMPTY + NF, B_CDONE = B_ZRDY + 1,
              B_EWRDY = B_CDONE + 2, B_PAIR = 80,
              B_IDX = B_PAIR + 13, B_FIN = B_PAIR + 14;
constexpr int OFF_TS = OFF_BAR + 768;
constexpr int SMEM = OFF_TS + 512;
static_assert(SMEM <= 232448, "smem");
constexpr int NFIRST = 4;
constexpr int NP = 2;
constexpr int NUNIT = 128;

__device__ __align__(1024) uint8_t g_wt[2 * NCHUNK * CHUNK];
__device__ unsigned int g_cnt;

__device__ __forceinline__ void u_lda(uint32_t (&A)[8], uint32_t a0, uint32_t a1) {
    ldsm_x4_t(a0, A[0], A[1], A[2], A[3]);
    ldsm_x4_t(a1, A[4], A[5], A[6], A[7]);
}
__device__ __forceinline__ void u_mma(float (&acc)[16], const uint32_t (&A)[8], uint64_t desc) {
    wgmma_m64n32k16_rs<2>(acc, A[0], A[1], A[2], A[3], desc);
    wgmma_m64n32k16_rs<1>(acc, A[4], A[5], A[6], A[7], desc + 64);
}
__device__ __forceinline__ void send_addr(uint32_t sb, int src, int w4, uint32_t& da, uint32_t& db, uint32_t& t) {
    uint32_t rb, l;
    asm volatile("mov.u32 %0, %%laneid;" : "=r"(l));
    asm volatile("mapa.shared::cluster.u32 %0, %1, %2;" : "=r"(rb) : "r"(sb), "r"(w4 >> 1));
    da = opq(rb + OFF_DP + (src * 32 + (w4 & 1) * 16 + 8 * (l & 1) + (l >> 2)) * 4);
    db = opq(rb + OFF_BAR + B_FIN * 8 + (l >> 5));
    t = l & 3;
}
__device__ __forceinline__ void send_partial(uint32_t da, uint32_t db, uint32_t t, float v0, float v1) {
    asm volatile("{\n.reg .pred p;\nsetp.lt.u32 p, %3, 2;\n@p st.async.weak.shared::cluster.mbarrier::complete_tx::bytes.f32 [%0], %1, [%2];\n}\n" ::"r"(da), "f"(t ? v1 : v0),
                 "r"(db), "r"(t)
                 : "memory");
}

__global__ void __cluster_dims__(2, 1, 1) __launch_bounds__(512, 1)
fused_kernel(const int* __restrict__ idx, const __nv_bfloat16* __restrict__ table, const __nv_bfloat16* __restrict__ w1, const __nv_bfloat16* __restrict__ w_bi,
             const __nv_bfloat16* __restrict__ w2, const __nv_bfloat16* __restrict__ w_cross, const __nv_bfloat16* __restrict__ se_w1,
             const __nv_bfloat16* __restrict__ se_w2, __nv_bfloat16* __restrict__ out, const __grid_constant__ CUtensorMap tmW1) {
    extern __shared__ __align__(1024) uint8_t smem_raw[];
    const int tid = threadIdx.x, b = (tid >> 3) & 31;
    const int pb0 = (blockIdx.x >> 1) * 64;
    int2 i0a, i0b, i1a, i1b;
    asm volatile("ld.global.nc.v2.u32 {%0,%1}, [%8];\nld.global.nc.v2.u32 {%2,%3}, [%8 + 3328];\nld.global.nc.v2.u32 {%4,%5}, [%8 + 8];\nld.global.nc.v2.u32 {%6,%7}, [%8 + 3336];"
                 : "=r"(i0a.x), "=r"(i0a.y), "=r"(i0b.x), "=r"(i0b.y), "=r"(i1a.x), "=r"(i1a.y), "=r"(i1b.x), "=r"(i1b.y)
                 : "l"(idx + (pb0 + b) * NF));
    const uint32_t sb = __shfl_sync(0xffffffffu, smem_u32(smem_raw), 0);
    const uint32_t bars = sb + OFF_BAR;
#define BAR(i) (bars + (i) * 8)
    const int warp = __shfl_sync(0xffffffffu, tid >> 5, 0), lane = tid & 31, g = lane >> 2, t = lane & 3;
    const int rank = blockIdx.x & 1;
    if (tid == 0) TS(0);
    if (elect_one()) {
        mbar_init(BAR(B_PAIR + warp), warp < 13 ? 256 + (warp == 10) : 1);
        if (warp >= 13) {
            asm volatile("fence.mbarrier_init.release.cluster;" ::: "memory");
            mbar_expect_tx(BAR(B_PAIR + warp), warp == 13 ? 64 * NF * 4 : 6 * 32 * 4);
            if (warp == 13) bulk_load(sb + OFF_IDX, idx + pb0 * NF, 64 * NF * 4, BAR(B_IDX));
        }
        if (warp == 6) asm volatile("cp.async.bulk.prefetch.L2.global [%0], %1;" ::"l"((const char*)w1 + 19 * 32768 + blockIdx.x * 1792), "n"(1792) : "memory");
        mbar_init(BAR(16 + warp), (warp & 1) || !warp ? 1 : 9);
        mbar_init(BAR(32 + warp), (warp & 1) && warp != 9 ? 1 : 9);
        mbar_init(BAR(48 + warp), 4);
        mbar_init(BAR(64 + warp), warp == B_CDONE - 64 ? 8 : 4);
        if (warp < 4 + NP) mbar_init(BAR(warp), warp < 4 ? (0x3421 >> (4 * warp)) & 7 : 256);
        asm volatile("fence.mbarrier_init.release.cluster;" ::: "memory");
    }
    __syncthreads();
    asm volatile("barrier.cluster.arrive.relaxed.aligned;" ::: "memory");
    if (tid == 0) TS(1);

    if (warp >= 12) {
        asm volatile("setmaxnreg.dec.sync.aligned.u32 %0;" ::"n"(R_PROD));
        if ((sb & 0xFFFFFFu) != SB0) __trap();
        if (warp == 12) {
            const uint32_t c0 = clock();
#pragma unroll 1
            for (int f = 0; f < NF; f++) {
                const uint32_t dist = w1_dist(f) * RT;
                if (f >= 5) mbar_wait_bounded(BAR(B_EMPTY + f - (f < 19 ? 5 : 4)), 0);
                while (f < 5 && (uint32_t)clock() - c0 < f * 450) __nanosleep(32);
                TSL(80 + f);
                if (elect_one()) {
                    mbar_expect_tx(BAR(B_W + f), HS_BYTES);
                    tma_load_3d(sb + OFF_WBI - 2 * dist, &tmW1, 0, f * 64, rank * 2, BAR(B_W + f));
                    tma_load_3d(sb + OFF_WBI - dist, &tmW1, 0, f * 64, rank * 2 + 1, BAR(B_W + f));
                }
            }
            asm volatile("barrier.cluster.wait.acquire.aligned;" ::: "memory");
            const uint64_t po = (uint64_t)(out + pb0 + 32 * rank + lane);
            const uint32_t plo = opq((uint32_t)po), phi = opq((uint32_t)(po >> 32) + (lane >> 5)), dp = opq(sb + OFF_DP + lane * 4);
            mbar_wait_bounded(BAR(B_FIN), 0);
            const uint4 u = make_uint4(lds32(dp), lds32(dp + 128), lds32(dp + 256), lds32(dp + 384));
            const uint2 v = make_uint2(lds32(dp + 512), lds32(dp + 640));
            asm volatile("st.global.u16 [%0], %1;" ::"l"(((uint64_t)phi << 32) | plo),
                         "h"(__bfloat16_as_ushort(__float2bfloat16_rn((__uint_as_float(u.x) + __uint_as_float(u.y)) + (__uint_as_float(u.z) + __uint_as_float(u.w)) +
                                                                      (__uint_as_float(v.x) + __uint_as_float(v.y)))))
                         : "memory");
            TSL(15);
        } else {
            if (warp == 13) {
                const uint32_t sr = sb + OFF_AP;
                {
                    uint32_t v[12];
#pragma unroll
                    for (int i = 0; i < 12; i++) v[i] = lane + 32 * (i >> 1) < NF * NFR / 2 ? __ldg(reinterpret_cast<const uint32_t*>((i & 1) ? se_w2 : se_w1) + lane + 32 * (i >> 1)) : 0u;
#pragma unroll
                    for (int i = 0; i < 12; i++) asm volatile("st.shared.u32 [%0], %1;" ::"r"(sr + lane * 4 + (i >> 1) * 128 + (i & 1) * 1024), "r"(v[i]) : "memory");
                    __syncwarp();
                }
#pragma unroll 1
                for (int q = 0; q < 8; q++) {
                    const int c1 = 8 * (q & 1) + g, o1 = c1 < NFR ? min((8 * (q >> 1) + 2 * t) * NFR + c1, NF * NFR) : NF * NFR;
                    const int c2 = 8 * (q & 3) + ((q & 3) < 3 ? 4 * (g & 1) + (g >> 1) : (g & 1)), o2 = min((8 * (q >> 2) + 2 * t) * NF + c2, NF * NFR);
                    uint32_t y1, y2;
                    asm volatile("{\n.reg .b16 a, b, c, d;\nld.shared.b16 a, [%2];\nld.shared.b16 b, [%2 + 26];\nld.shared.b16 c, [%3 + 1024];\nld.shared.b16 d, [%3 + 1076];\n"
                                 "mov.b32 %0, {a, b};\nmov.b32 %1, {c, d};\n}\n" : "=r"(y1), "=r"(y2) : "r"(sr + 2 * o1), "r"(sr + 2 * o2));
                    asm volatile("st.shared.u32 [%0], %1;\nst.shared.u32 [%0 + 1024], %2;" ::"r"(sb + OFF_SEF + q * 128 + lane * 4), "r"(y1),
                                 "r"(hmul2_bf16(y2, 0x3E803E80u))
                                 : "memory");
                }
                fence_proxy_async();
                __syncwarp();
                TSL(12);
                if (elect_one()) mbar_arrive(BAR(B_PAIR + 10));
            } else if (warp == 15) {
                {
                    const int pq = blockIdx.x >> 6, js = (blockIdx.x >> 1) & 31;
                    const int j = js < 24 ? (js & 24) + 4 * (js & 1) + ((js >> 1) & 3) : 24 + (js & 1);
                    const bool on = js < 24 || ((js >> 1) & 3) == ((lane >> 2) & 3);
                    const __nv_bfloat16* s = w_cross + ((size_t)(pq * NF) * NF + j) * ND + 32 * rank + lane;
                    uint8_t* d = g_wt + (size_t)rank * NCHUNK * CHUNK + (((lane & 15) >> 1) * 2 + (lane >> 4)) * CHUNK + ((lane & 1) * 2 + pq) * TILE + js * 16;
#pragma unroll 1
                    for (int kh = 0; kh < 2; kh++) {
                        uint32_t x[8];
#pragma unroll
                        for (int k = 0; k < 8; k++)
                            x[k] = (on && (kh == 0 || k < 5)) ? ldg_u16(s + (k + (k & 4)) * NF * ND) | (ldg_u16(s + (k == 4 && kh ? 9 : k + (k & 4) + 4) * NF * ND) << 16) : 0u;
                        *reinterpret_cast<uint4*>(d) = make_uint4(x[0], x[1], x[2], x[3]);
                        *reinterpret_cast<uint4*>(d + 512) = make_uint4(x[4], x[5], x[6], x[7]);
                        s += 16 * NF * ND;
                        d += 1024;
                    }
                    __syncwarp();
                }
                TSL(8);
                if (elect_one()) asm volatile("red.release.gpu.global.inc.u32 [%0], %1;" ::"l"(&g_cnt), "n"(NUNIT + 127) : "memory");
                TSL(9);
                mbar_wait(BAR(B_EMPTY + 6), 0);
                TSL(10);
                unsigned int v;
                do {
                    asm volatile("ld.acquire.gpu.global.u32 %0, [%1];" : "=r"(v) : "l"(&g_cnt) : "memory");
                } while (v < NUNIT);
                asm volatile("fence.proxy.async.global;" ::: "memory");
                __syncwarp();
                if (elect_one()) asm volatile("red.relaxed.gpu.global.inc.u32 [%0], %1;" ::"l"(&g_cnt), "n"(NUNIT + 127) : "memory");
                TSL(11);
                const uint8_t* wsrc = g_wt + (size_t)rank * NCHUNK * CHUNK;
                static_for<0, 10>([&](auto KC) {
                    constexpr int k = decltype(KC)::value, T[10][4] = {{0, 2, 5, 0}, {10, 1, 12, 2}, {2, 2, 8, 1}, {4, 2, 9, 1}, {6, 2, 10, 2}, {8, 2, 10, 2}, {11, 1, 11, 2}, {12, 1, 11, 3}, {13, 1, 11, 3}, {14, 2, 13, 3}};
                    if (k == 0 || T[k][2] != T[k ? k - 1 : 0][2]) mbar_wait(BAR(B_EMPTY + 14 + T[k][2]), 0);
                    TSL(30 + k);
                    if (elect_one()) {
                        mbar_expect_tx(BAR(B_CFULL + T[k][3]), T[k][1] * CHUNK);
                        bulk_load(sb + OFF_RT + (13 + ((int)(CPOS >> (4 * T[k][0])) & 15)) * RT, wsrc + T[k][0] * CHUNK, T[k][1] * CHUNK, BAR(B_CFULL + T[k][3]));
                    }
                });
            }
            __syncwarp();
            asm volatile("barrier.cluster.wait.acquire.aligned;" ::: "memory");
        }
    } else if (warp < 4) {
        {
            const uint4* wb = reinterpret_cast<const uint4*>(w_bi + (tid >> 2) * 64 + 32 * rank + 8 * t);
            const uint4 wb0 = __ldg(wb), wb1 = __ldg(wb + 256);
            const uint32_t w2v = __ldg(reinterpret_cast<const uint32_t*>(w2) + rank * 64 + (tid & 63));
            sts128(sb + OFF_WBI + (tid & 63) * 128 + ((4 ^ (tid & 7)) << 4), 0x3C803C80u, 0x3C803C80u, 0x3C803C80u, 0x3C803C80u);
            asm volatile("st.shared.u32 [%0], %1;" ::"r"(sb + OFF_ID + (tid & 63) * 4), "r"(0x3F803F80u) : "memory");
            asm volatile("st.shared.u32 [%0], %1;" ::"r"(sb + OFF_W2 + (tid & 63) * 4), "r"(w2v) : "memory");
            const uint32_t wd = sb + OFF_WBI + (tid >> 2) * 128 + ((t ^ (g & 7)) << 4);
            sts128(wd, wb0.x, wb0.y, wb0.z, wb0.w);
            sts128(wd + 4096, wb1.x, wb1.y, wb1.z, wb1.w);
            fence_proxy_async();
        }
        asm volatile("setmaxnreg.inc.sync.aligned.u32 %0;" ::"n"(R_DEEP));
        asm volatile("bar.sync 1, 128;" ::: "memory");
        asm volatile("barrier.cluster.wait.acquire.aligned;" ::: "memory");
        TS(7);
        float acc[2][84], e2[2][20], ad[64];
#pragma unroll
        for (int i = 0; i < 84; i++) asm volatile("" : "=f"(acc[0][i]), "=f"(acc[1][i]));
        const uint32_t sa = opq(sb + OFF_EW + (lane >> 4) * 128 + (2 * warp + ((lane >> 3) & 1)) * 512 + (lane & 7) * 16);
        const uint32_t ln = opq(lane);
        const bool l0 = ln == 0;
        uint32_t za[8];
#pragma unroll
        for (int i = 0; i < 6; i++) asm volatile("" : "=r"(za[i]));
        auto cvt = [&](uint32_t (&pk)[8], int f) {
            const float* e = f < 22 ? acc[f & 1] + 64 : e2[f & 1];
#pragma unroll
            for (int i = 0; i < 8; i++) asm volatile("cvt.rn.bf16x2.f32 %0, %1, %2;" : "=r"(pk[i]) : "f"(e[2 * i + 1]), "f"(e[2 * i]));
            uint32_t &z0 = za[2 * (f >> 3)], &z1 = za[2 * (f >> 3) + 1];
            asm volatile("{\n.reg .pred p;\nsetp.eq.u32 p, %6, %7;\n@p cvt.rn.bf16x2.f32 %0, %2, %4;\n@p cvt.rn.bf16x2.f32 %1, %3, %5;\n}\n"
                         : "+r"(z0), "+r"(z1)
                         : "f"(e[16]), "f"(e[18]), "f"((f & 1) ? __uint_as_float(z0) : 0.f), "f"((f & 1) ? __uint_as_float(z1) : 0.f), "r"(ln & 3), "r"((f >> 1) & 3));
        };
        auto store = [&](const uint32_t (&pk)[8], int f) {
            stsm_x4_t(sa + f * EWP, pk[0], pk[1], pk[2], pk[3]);
            stsm_x4_t(sa + f * EWP + 256, pk[4], pk[5], pk[6], pk[7]);
        };
        auto da = [](int f, int i) { return make_desc(SB0 + OFF_RT + tile(f) * RT, 16, 1024, 1) + 2 * (i ^ (2 * (f & 1))); };
        auto db = [](int f, int i) { return make_desc(SB0 + OFF_WBI - 2 * w1_dist(f) * RT, w1_dist(f) * RT, 1024, 1) + 128 * i; };
        auto mma_e = [&](int f) {
            wgmma_fence();
#pragma unroll
            for (int i = 0; i < 4; i++) {
                if (i) wgmma_n40(e2[f & 1], da(f, i), make_desc(SB0 + OFF_WBI, RT, 1024, 1) + 128 * i, 1);
                else wgmma_n40_0(e2[f & 1], da(f, i), make_desc(SB0 + OFF_WBI, RT, 1024, 1));
            }
            wgmma_commit();
        };
        auto mma_d = [&](int f, int i0, int i1) {
#pragma unroll
            for (int i = i0; i < i1; i++) wgmma_n128(ad, da(f, i), db(f, i), 1);
            wgmma_commit();
        };
#define ROWS_TO_ASYNC() asm volatile("fence.proxy.async::generic.acquire.sync_restrict::shared::cluster.cluster;" ::: "memory")
#define SYNC4() asm volatile("bar.sync 1, 128;" ::: "memory")
        uint32_t pk[8];
        static_for<0, 22>([&](auto KC) {
            constexpr int k = decltype(KC)::value;
            if (k > 1) {
                wgmma_wait<1>();
                if (l0) mbar_arrive(BAR(B_EMPTY + k - 2));
                cvt(pk, k - 2);
#pragma unroll
                for (int i = 64; i < 83; i++)
                    if (i != 81) asm volatile("mul.f32 %0, %0, 0f00000000;" : "+f"(acc[k & 1][i]));
            }
            if (k < 2 * NP || !(k & 1)) mbar_wait(BAR((k < 2 * NP && !(k & 1) ? B_F : B_PAIR) + k / 2), 0);
            mbar_wait(BAR(B_W + k), 0);
            ROWS_TO_ASYNC();
            if (k == 0) TS(19);
            wgmma_fence();
#pragma unroll
            for (int i = 0; i < 4; i++) wgmma_n168(acc[k & 1], da(k, i), db(k, i), k > 1 || i);
            wgmma_commit();
            if (k > 1) {
                SYNC4();
                store(pk, k - 2);
            }
        });
        {
            uint32_t p2[8], p3[8], p4[8];
            wgmma_wait<1>();
            if (l0) mbar_arrive(BAR(B_EMPTY + 20));
            cvt(pk, 20);
            mbar_wait(BAR(B_PAIR + 11), 0);
            mbar_wait(BAR(B_PAIR + 12), 0);
            mbar_wait(BAR(B_W + 22), 0);
            ROWS_TO_ASYNC();
            mma_e(22);
            SYNC4();
            store(pk, 20);
            wgmma_wait<1>();
            if (l0) mbar_arrive(BAR(B_EMPTY + 21));
            cvt(pk, 21);
#pragma unroll
            for (int i = 0; i < 64; i++) asm volatile("add.f32 %0, %1, %2;" : "=f"(ad[i]) : "f"(acc[0][i]), "f"(acc[1][i]));
            wgmma_fence();
            mma_d(22, 0, 1);
            mma_e(23);
            store(pk, 21);
            wgmma_wait<2>();
            cvt(p2, 22);
            mma_e(24);
            SYNC4();
            store(p2, 22);
            wgmma_wait<1>();
            cvt(p3, 23);
            mma_e(25);
            mma_d(22, 1, 3);
            store(p3, 23);
            wgmma_wait<1>();
            if (l0) mbar_arrive(BAR(B_ZRDY));
            TS(2);
            za[6] = za[7] = 0u;
            cvt(pk, 24);
            cvt(p4, 25);
#pragma unroll
            for (int i = 0; i < 6; i++) za[i] |= p4[7] & (ln >> 5);
            constexpr uint64_t d1 = make_desc(SB0 + OFF_SEF, 256, 128, 0), d2 = make_desc(SB0 + OFF_SEF + 1024, 512, 128, 0);
            float h[8], o[16];
#pragma unroll
            for (int i = 0; i < 16; i++) asm volatile("" : "=f"(o[i]), "=f"(h[i & 7]));
            wgmma_fence();
            wgmma_m64n16k16_rs<0>(h, za, d1);
            wgmma_m64n16k16_rs<1>(h, za + 4, d1 + 32);
            wgmma_commit();
            mma_d(22, 3, 4);
            mbar_wait(BAR(B_W + 23), 0);
            wgmma_fence();
            mma_d(23, 0, 4);
            wgmma_wait<2>();
            const uint32_t ha0 = pack_bf16(gelu2(h[0]), gelu2(h[1])), ha1 = pack_bf16(gelu2(h[2]), gelu2(h[3])), ha2 = pack_bf16(gelu2(h[4]), gelu2(h[5])),
                           ha3 = pack_bf16(gelu2(h[6]), gelu2(h[7]));
            wgmma_fence();
            wgmma_m64n32k16_rs<2>(o, ha0, ha1, ha2, ha3, d2);
            wgmma_commit();
            wgmma_wait<2>();
            if (l0) mbar_arrive(BAR(B_EMPTY + 22));
            mbar_wait(BAR(B_W + 24), 0);
            wgmma_fence();
            mma_d(24, 0, 4);
            wgmma_wait<1>();
            if (l0) mbar_arrive(BAR(B_EMPTY + 23));
            mbar_wait(BAR(B_W + 25), 0);
            wgmma_fence();
            mma_d(25, 0, 4);
            SYNC4();
            store(pk, 24);
            store(p4, 25);
#pragma unroll
            for (int i = 0; i < 2; i++) {
                uint32_t a[4];
#pragma unroll
                for (int k = 0; k < 4; k++) a[k] = pack_bf16(fmaf(tanh_fast(o[8 * i + 2 * k]), 0.5f, 0.5f), fmaf(tanh_fast(o[8 * i + 2 * k + 1]), 0.5f, 0.5f));
                sts128(sb + OFF_AP + i * 2048 + warp * 512 + ln * 16, a[0], a[1], a[2], a[3]);
            }
            __syncwarp();
            if (l0) mbar_arrive(BAR(B_EWRDY));
            wgmma_wait<1>();
            if (l0) mbar_arrive(BAR(B_EMPTY + 24));
            TS(3);
        }
        {
            wgmma_wait<0>();
            if (l0) mbar_arrive(BAR(B_EMPTY + 25));
            uint32_t hw[32];
#pragma unroll
            for (int i = 0; i < 32; i++) asm volatile("cvt.rn.bf16x2.f32 %0, %1, %2;" : "=r"(hw[i]) : "f"(ad[2 * i + 1]), "f"(ad[2 * i]));
            asm volatile("setmaxnreg.dec.sync.aligned.u32 %0;" ::"n"(R_DEEP2));
            TS(4);
            float o[4];
#pragma unroll
            for (int i = 0; i < 4; i++) asm volatile("" : "=f"(o[i]));
#pragma unroll
            for (int i = 0; i < 32; i++) hw[i] = gelu2p(hw[i]);
            wgmma_fence();
#pragma unroll
            for (int it = 0; it < 8; it++) wgmma_m64n8k16_rs(o, hw + 4 * it, make_desc(SB0 + OFF_W2, 16, 128, 0) + 2 * it, it);
            wgmma_commit();
            wgmma_wait<0>();
            o[2] = __shfl_sync(0xffffffffu, o[2], ln & 28);
            uint32_t da, db, tt;
            send_addr(sb, rank * 3, warp, da, db, tt);
            send_partial(da, db, tt, 0.5f * o[0], 0.5f * o[2]);
        }
        TS(5);
    } else {
        const int wgc = (warp >> 2) - 1, w4 = warp & 3;
        const char* so = (const char*)table + 16 * (lane & 7);
        auto rp = [&](uint32_t i) { return row_ptr(so, i); };
        const uint32_t d0 = opq(sb + OFF_RT + b * 128 + (((lane ^ b) & 7) << 4)), d1 = opq((d0 ^ 64) + 6 * RT);
        uint32_t c0;
        auto until = [&](int f) {
            for (;;) {
                uint32_t c;
                asm volatile("mov.u32 %0, %%clock;" : "=r"(c)::"memory");
                if (c - c0 >= f * 300 - 200) break;
                __nanosleep(32);
            }
        };
        {
            const int ia[4] = {i0a.x, i0a.y, i1a.x, i1a.y}, ib[4] = {i0b.x, i0b.y, i1b.x, i1b.y};
            static_for<0, NFIRST>([&](auto FC) {
                constexpr int f = decltype(FC)::value, o = (f >> 1) * RT;
                if (f) until(f);
                cp_async16(((f & 1) ? d1 : d0) + o, rp(ia[f]));
                cp_async16(((f & 1) ? d1 : d0) + o + 4096, rp(ib[f]));
                cp_async_mbar_arrive_noinc(BAR(((f & 1) ? B_PAIR : B_F) + (f >> 1)));
                if (f == 0) asm volatile("mov.u32 %0, %%clock;" : "=r"(c0)::"memory");
            });
            if (wgc == 0) TS(6);
        }
        asm volatile("setmaxnreg.inc.sync.aligned.u32 %0;" ::"n"(R_CR1));
        uint32_t M[8][12], y[4][2];
        {
            const uint32_t pa = opq(sb + OFF_RT + (t & 1) * 6 * RT + (16 * w4 + g) * 128 + (((4 * rank + 2 * wgc) ^ g ^ (4 * (t & 1))) << 4)), t1 = opq(t >> 1);
            const uint32_t ia = opq(sb + OFF_IDX + b * NF * 4);
#pragma unroll
            for (int i = 0; i < 96; i++) asm volatile("" : "=r"(M[i / 12][i % 12]));
            mbar_wait(BAR(B_IDX), 0);
            uint32_t x[13][4];
#pragma unroll
            for (int p = 2; p < 13; p++)
                asm volatile("ld.shared.v2.u32 {%0,%1}, [%4];\nld.shared.v2.u32 {%2,%3}, [%4 + 3328];" : "=r"(x[p][0]), "=r"(x[p][2]), "=r"(x[p][1]), "=r"(x[p][3]) : "r"(ia + p * 8));
            const uint32_t pb = opq(pa ^ 16);
            auto conv = [&](int G) {
#pragma unroll
                for (int i = 0; i < 16; i++) {
                    uint32_t &u = M[i >> 1][4 * G + 2 * (i & 1)], &v = M[i >> 1][4 * G + 2 * (i & 1) + 1];
                    asm volatile("{\n.reg .b32 t;\nprmt.b32 t, %0, %1, 0x5410;\nprmt.b32 %1, %0, %1, 0x7632;\nmov.b32 %0, t;\n}\n" : "+r"(u), "+r"(v));
                }
#pragma unroll
                for (int i = 0; i < 8; i++)
                    asm volatile("{\n.reg .pred p;\nsetp.eq.u32 p, %5, 2;\n@p st.shared.v4.u32 [%4], {%0,%1,%2,%3};\n}\n" ::"r"(M[i & 4][4 * G + (i & 3)]), "r"(M[(i & 4) + 1][4 * G + (i & 3)]),
                                 "r"(M[(i & 4) + 2][4 * G + (i & 3)]), "r"(M[(i & 4) + 3][4 * G + (i & 3)]), "r"(pa), "r"(t1));
            };
            auto gather = [&](auto PC) {
                constexpr int p = decltype(PC)::value;
                constexpr uint32_t o1 = (tile(2 * p + 1) - 6) * RT;
                if (p < 6) until(2 * p);
                cp_async16(d0 + tile(2 * p) * RT, rp(x[p][0]));
                cp_async16(d0 + tile(2 * p) * RT + 4096, rp(x[p][1]));
                if (p < NP) cp_async_mbar_arrive_noinc(BAR(B_F + p));
                if (p < 6) until(2 * p + 1);
                cp_async16(d1 + o1, rp(x[p][2]));
                cp_async16(d1 + o1 + 4096, rp(x[p][3]));
                cp_async_mbar_arrive_noinc(BAR(B_PAIR + p));
            };
            auto pick = [&](auto QC) {
                constexpr int q = decltype(QC)::value, c = 4 * (q >> 2) + ((q >> 1) & 1);
#pragma unroll
                for (int i = 0; i < 4; i++)
                    asm volatile("{\n.reg .pred p;\nsetp.eq.u32 p, %5, %6;\n@p ld.shared.v4.u32 {%0,%1,%2,%3}, [%4];\n}\n"
                                 : "+r"(M[2 * (i & 2)][c + 2 * (i & 1)]), "+r"(M[2 * (i & 2) + 1][c + 2 * (i & 1)]), "+r"(M[2 * (i & 2) + 2][c + 2 * (i & 1)]),
                                   "+r"(M[2 * (i & 2) + 3][c + 2 * (i & 1)])
                                 : "r"(((i & 2) ? pb : pa) + tile(2 * q) * RT + (i & 1) * 1024 + (tile(2 * q + 1) - 6 - tile(2 * q)) * (t & 1) * RT), "r"(t1), "n"(q & 1));
                __syncwarp();
                if (elect_one()) mbar_arrive(BAR(B_W + 2 * q + 2));
                if (q == 4 || q == 8) conv(q / 4 - 1);
            };
#define IC(x) std::integral_constant<int, x>{}
            gather(IC(2));
            gather(IC(3));
            static_for<0, 3>([&](auto QC) {
                constexpr int q = decltype(QC)::value;
                mbar_wait(BAR(B_PAIR + q), 0);
                pick(QC);
                if constexpr (q < 2) gather(IC(q + 4));
            });
            static_for<3, 12>([&](auto QC) {
                constexpr int q = decltype(QC)::value, p = q < 7 ? q + 3 : q == 8 ? 10 : q == 11 ? 12 : 0;
                if (q == 10) {
                    mbar_wait(BAR(B_EMPTY + 14), 0);
                    gather(IC(11));
                }
                mbar_wait(BAR(B_EMPTY + 2 * q - 5 - (q == 11)), 0);
                if constexpr (p == 12) gather(IC(12));
                mbar_wait(BAR(B_PAIR + q), 0);
                if constexpr (p && p < 12) gather(IC(p));
                if (q == 9) {
#pragma unroll
                    for (int i = 0; i < 4; i++) asm volatile("prefetch.global.L2 [%0];" ::"l"(rp(rank ? x[11 + (i >> 1)][2 * (i & 1) + 1] : x[11 + (i >> 1)][2 * (i & 1)])));
                }
                pick(QC);
            });
            const uint32_t ta = sb + OFF_RT + tile(24) * RT + (16 * w4 + g) * 128 + (((4 * rank + 2 * wgc + (t >> 1)) ^ g) << 4) + 8 * (t & 1);
            mbar_wait(BAR(B_PAIR + 12), 0);
#pragma unroll
            for (int k = 0; k < 4; k++) asm volatile("ld.shared.v2.u32 {%0,%1}, [%2];" : "=r"(y[k][0]), "=r"(y[k][1]) : "r"(((k & 1) ? (ta ^ 64) - (tile(24) - tile(25)) * RT : ta) + (k >> 1) * 1024));
            __syncwarp();
            if (elect_one()) mbar_arrive(BAR(B_W + 25));
            conv(2);
        }
        uint32_t TL[4][2];
        uint32_t ap[8], a0, a1;
        uint32_t A0[8], A1[8], Aq[8], w[4], aq;
        {
            const int r = lane & 7, bh = (lane >> 3) & 1, ig = lane >> 4;
            const uint32_t x = sb + OFF_EW + wgc * 256 + (2 * w4 + bh) * 512 + (8 * ig + 4 * (r & 1) + (r >> 1)) * EWP;
            a0 = opq(x);
            a1 = opq(x + (!ig || r == 0 ? 16 : r == 1 ? 13 : r == 2 ? 11 : 8) * EWP);
            aq = opq(sb + OFF_AP + w4 * 512 + lane * 16);
        }
        asm volatile("barrier.cluster.wait.acquire.aligned;" ::: "memory");
        mbar_wait(BAR(B_CFULL), 0);
        mbar_wait(BAR(B_EWRDY), 0);
        u_lda(A0, a0, a1);
#pragma unroll
        for (int i = 0; i < 2; i++) {
            const uint4 v = lds128(aq + i * 2048);
            ap[4 * i] = v.x, ap[4 * i + 1] = v.y, ap[4 * i + 2] = v.z, ap[4 * i + 3] = v.w;
        }
        if (wgc == 0) TS(60);
        asm volatile("setmaxnreg.inc.sync.aligned.u32 %0;" ::"n"(R_CR2));
        if (wgc == 0) TS(61);
        asm volatile("mov.u32 %0, %%clock;\nand.b32 %0, %0, %1;" : "=r"(aq) : "r"(warp >> 4));
        a0 |= aq, a1 |= aq;
#pragma unroll
        for (int k = 0; k < 8; k++) {
            TL[k >> 1][k & 1] = __byte_perm(y[2 * (k & 1)][k >> 2], y[2 * (k & 1) + 1][k >> 2], (0x5410 + 0x2222 * ((k >> 1) & 1)) | aq);
            ap[k] |= aq, A0[k] |= aq & TL[k >> 1][k & 1];
        }
        constexpr uint64_t dt = make_desc(SB0 + OFF_RT + 13 * RT, 512, 128, 0), dqc = make_desc(SB0 + OFF_ID, 128, 128, 0);
        const uint64_t dq = uni64(dqc + (sb >> 28));
        auto dsc = [&](int e, int pq) {
            const int s0 = (int)(CPOS >> (8 * (e >> 1))) & 15, s1 = (int)(CPOS >> (8 * (e >> 1) + 4)) & 15;
            return dt + (s0 + wgc * (s1 - s0)) * (CHUNK >> 4) + ((e & 1) * 2 + pq) * (TILE >> 4);
        };
        float S[4], accP[16], accQ[16];
#pragma unroll
        for (int i = 0; i < 16; i++) asm volatile("" : "=f"(accP[i]), "=f"(accQ[i]));
        u_lda(A1, a0 + 16, a1 + 16);
#pragma unroll
        for (int i = 0; i < 4; i++) asm volatile("" : "=f"(S[i]));
#pragma unroll
        for (int k = 0; k < 8; k++) Aq[k] = hmul2_bf16(A0[k], ap[k]);
        wgmma_fence();
        u_mma(accP, A0, dsc(0, 0));
        wgmma_commit();
        u_mma(accQ, Aq, dsc(0, 1));
        wgmma_commit();
        if (wgc == 0) TS(62);
        auto pack8 = [&](uint32_t (&d)[8], const float (&a)[16]) {
#pragma unroll
            for (int k = 0; k < 8; k++) asm volatile("cvt.rn.bf16x2.f32 %0, %1, %2;" : "=r"(d[k]) : "f"(a[2 * k + 1]), "f"(a[2 * k]));
        };
        uint32_t da, db, tt;
        static_for<0, 8>([&](auto PC) {
            constexpr int p = decltype(PC)::value, e = 2 * p;
            if (p == 7) send_addr(sb, rank * 3 + 1 + wgc, w4, da, db, tt);
            auto mw = [&](int s, int k) { return k < 6 ? M[p][2 * k + s] : TL[(e + s) & 3][k - 6]; };
            uint32_t tp[8], tq[8];
            wgmma_wait<1>();
            pack8(tp, accP);
            wgmma_fence();
            u_mma(accP, A1, dsc(e + 1, 0));
            if (p) {
                wgmma_m64n8k16_rs(S, w, dq, p > 1);
            }
            wgmma_commit();
            wgmma_wait<1>();
            if (p < 7) u_lda(A0, a0 + 16 * e + 32, a1 + 16 * e + 32);
            pack8(tq, accQ);
#pragma unroll
            for (int k = 0; k < 8; k++) Aq[k] = hmul2_bf16(A1[k], ap[k]);
            wgmma_fence();
            u_mma(accQ, Aq, dsc(e + 1, 1));
            wgmma_commit();
#pragma unroll
            for (int k = 0; k < 8; k++) tq[k] = hfma2_bf16(tq[k], ap[k], tp[k]);
            if (p == 0 || p == 2 || p == 5) mbar_wait(BAR(B_CFULL + 1 + p / 2), 0);
            wgmma_wait<1>();
            pack8(tp, accP);
            if (p < 7) {
                wgmma_fence();
                u_mma(accP, A0, dsc(e + 2, 0));
                wgmma_commit();
            }
#pragma unroll
            for (int k = 0; k < 8; k++) w[k & 3] = k > 3 ? hfma2_bf16(tq[k], mw(0, k), w[k & 3]) : hmul2_bf16(tq[k], mw(0, k));
            wgmma_wait<(p < 7)>();
            if (p < 7) u_lda(A1, a0 + 16 * e + 48, a1 + 16 * e + 48);
            if (p == 0 && elect_one()) mbar_arrive(BAR(B_CDONE));
            pack8(tq, accQ);
            if (p < 7) {
#pragma unroll
                for (int k = 0; k < 8; k++) Aq[k] = hmul2_bf16(A0[k], ap[k]);
                wgmma_fence();
                u_mma(accQ, Aq, dsc(e + 2, 1));
                wgmma_commit();
            }
#pragma unroll
            for (int k = 0; k < 8; k++) w[k & 3] = hfma2_bf16(hfma2_bf16(tq[k], ap[k], tp[k]), mw(1, k), w[k & 3]);
        });
        wgmma_fence();
        wgmma_m64n8k16_rs(S, w, dq, 1);
        wgmma_commit();
        wgmma_wait<0>();
        send_partial(da, db, tt, S[0], S[2]);
        if (wgc == 0) TS(14);
    }
#undef BAR
}

typedef CUresult (*PFN_encodeTiled)(CUtensorMap*, CUtensorMapDataType, cuuint32_t, void*, const cuuint64_t*, const cuuint64_t*,
                                    const cuuint32_t*, const cuuint32_t*, CUtensorMapInterleave, CUtensorMapSwizzle,
                                    CUtensorMapL2promotion, CUtensorMapFloatOOBfill);

}

extern "C" void kernel_launch(void* const* d_in, const int* in_sizes, int n_in, void* d_out, int out_size) {
    const int* idx = (const int*)d_in[0];
    const __nv_bfloat16* table = (const __nv_bfloat16*)d_in[1];
    const __nv_bfloat16* se_w1 = (const __nv_bfloat16*)d_in[2];
    const __nv_bfloat16* se_w2 = (const __nv_bfloat16*)d_in[3];
    const __nv_bfloat16* w_bi = (const __nv_bfloat16*)d_in[4];
    const __nv_bfloat16* w_cross = (const __nv_bfloat16*)d_in[5];
    const __nv_bfloat16* w_deep1 = (const __nv_bfloat16*)d_in[6];
    const __nv_bfloat16* w_deep2 = (const __nv_bfloat16*)d_in[7];
    __nv_bfloat16* out = (__nv_bfloat16*)d_out;

    static PFN_encodeTiled enc = nullptr;
    if (!enc) {
        void* fn = nullptr;
        cudaDriverEntryPointQueryResult qres;
        cudaGetDriverEntryPoint("cuTensorMapEncodeTiled", &fn, cudaEnableDefault, &qres);
        enc = (PFN_encodeTiled)fn;
        cudaFuncSetAttribute(fused_kernel, cudaFuncAttributeMaxDynamicSharedMemorySize, SMEM);
    }
    CUtensorMap tm;
    {
        cuuint64_t gdim[3] = {64, (cuuint64_t)(NF * ND), 4};
        cuuint64_t gstr[2] = {(cuuint64_t)NH * 2, 128};
        cuuint32_t box[3] = {64, 64, 1};
        cuuint32_t estr[3] = {1, 1, 1};
        enc(&tm, CU_TENSOR_MAP_DATA_TYPE_BFLOAT16, 3, (void*)w_deep1, gdim, gstr, box, estr, CU_TENSOR_MAP_INTERLEAVE_NONE,
            CU_TENSOR_MAP_SWIZZLE_128B, CU_TENSOR_MAP_L2_PROMOTION_L2_256B, CU_TENSOR_MAP_FLOAT_OOB_FILL_NONE);
    }
    fused_kernel<<<128, 512, SMEM>>>(idx, table, w_deep1, w_bi, w_deep2, w_cross, se_w1, se_w2, out, tm);
}
```
